```python
import torch

def _softmax(x, axis=-1):
    return torch.softmax(x, dim=axis)
def _gelu(x):
    return torch.nn.functional.gelu(x, approximate="tanh")
def _silu(x):
    return torch.nn.functional.silu(x)
def _sigmoid(x):
    return torch.sigmoid(x)
def _layernorm(x, axis=-1, eps=1e-5):
    m = x.mean(dim=axis, keepdim=True)
    v = x.var(dim=axis, keepdim=True, unbiased=False)
    return (x - m) / torch.sqrt(v + eps)
def _scatter_add(tgt, idx, src, axis=0):
    return tgt.clone().index_add_(axis, idx, src)
def _segment_sum(src, seg, n):
    out = torch.zeros((n,) + src.shape[1:], dtype=src.dtype)
    return out.index_add_(0, seg, src)
def _pad(x, pw):
    flat = tuple(v for pair in reversed(pw) for v in pair)
    return torch.nn.functional.pad(x, flat)

kernel_name = 'standalone__deep_cross_xdeepfm__recsys'

def setup_inputs():

    _w = (lambda a: (lambda t: t.to(torch.bfloat16) if t.is_floating_point() else t)(torch.as_tensor(a)))
    B, F, D, L = 1024, 26, 128, 6
    V = min(1000000, 100000)
    Din = F * D
    return {
        "idx": _w((lambda lo, hi, *s: torch.randint(lo, hi, s))(0, V, B, F).to(torch.int64)),
        "table": _w((lambda *s: torch.randn(*s, dtype=torch.bfloat16) * 0.8)(V, D)),
        "ws_cin": _w((lambda *s: torch.randn(*s, dtype=torch.bfloat16) * 0.1)(L, F, F, F) * (1.0 / F)),
        "w_cin_out": _w((lambda *s: torch.randn(*s, dtype=torch.bfloat16) * 0.1)(L * F) * ((L * F) ** -0.5)),
        "w_dnn1": _w((lambda *s: torch.randn(*s, dtype=torch.bfloat16) * 0.8)(Din, Din) * (Din ** -0.5)),
        "b_dnn1": _w((lambda *s: torch.randn(*s, dtype=torch.bfloat16) * 1.6)(Din) * 0.1),
        "w_dnn2": _w((lambda *s: torch.randn(*s, dtype=torch.bfloat16) * 0.1)(Din) * (Din ** -0.5)),
        "b_out": _w((lambda *s: torch.randn(*s, dtype=torch.bfloat16) * 0.1)(1)),
    }

def reference(idx, table, ws_cin, w_cin_out, w_dnn1, b_dnn1, w_dnn2, b_out):
    x0 = table[idx]
    B = x0.shape[0]
    L = ws_cin.shape[0]
    xk = x0
    pooled = []
    for l in range(L):
        xk = torch.einsum('bid,bjd,hij->bhd', xk, x0, ws_cin[l])
        pooled.append(xk.sum(axis=-1))
    p_plus = torch.stack(pooled, axis=1).reshape(B, -1)
    logit_cin = p_plus @ w_cin_out
    h = x0.reshape(B, -1)
    h = _gelu(h @ w_dnn1 + b_dnn1)
    logit_dnn = h @ w_dnn2
    return logit_cin + logit_dnn + b_out
```

```cpp
#include <cuda_runtime.h>
#include <cuda_bf16.h>
#include <cuda.h>
#include <stdint.h>
#include <type_traits>

#define XD_W5 0
#define XD_B1 1
namespace {

constexpr int kB = 1024, kF = 26, kDin = 3328;
constexpr int kCtas = 132, kPrepCtas = 28, kGemmCtas = 104, kThreads = 384;
constexpr int kStages = 4, kStageBytes = 49152, kABytes = 16384, kKBlocks = 52;
constexpr int kNTiles = 13;

constexpr int kStepsS = 24, kStepsL = 43;
constexpr int kImgSBytes = kStepsS * 56 * 32;
constexpr int kImgLBytes = kStepsL * 32 * 32;
constexpr int kImgF2 = kImgSBytes, kImgB3 = kImgF2 + kImgLBytes, kImgF3 = kImgB3 + kImgLBytes;
constexpr int kImgBytes = kImgF3 + kImgLBytes;

#define XD_GEMM_TILES 12
constexpr int kGemmTiles = XD_GEMM_TILES;
constexpr int kPrepTilesTotal = 2 * kB - kGemmCtas * kGemmTiles;
constexpr int kPrepBase = kPrepTilesTotal / kPrepCtas, kPrepRem = kPrepTilesTotal % kPrepCtas;
constexpr int kMaxSamples = 18, kSlots = 20;
static_assert(kPrepBase / 2 + 2 <= kMaxSamples && kGemmTiles / 2 + 1 <= kMaxSamples, "sample table too small");

constexpr int kXPitch = 144, kXBufBytes = 27 * kXPitch;
constexpr int kOffRed = kImgBytes;
constexpr int kOffX = kStages * kStageBytes;
constexpr int kOffEpi = kOffX + 6 * kXBufBytes;
constexpr int kOffIdx = kOffEpi + 2048;
constexpr int kOffDnn = kOffIdx + (kMaxSamples + 2) * kF * 4 + 64;
constexpr int kOffBar = kOffDnn + kMaxSamples * kSlots * 4;
constexpr int kSmemBytes = kOffBar + 256 + 1024;
static_assert(kOffRed + 2 * kMaxSamples * 512 <= kOffX && kOffEpi % 16 == 0 && kOffDnn % 16 == 0 && kOffBar % 8 == 0, "layout");

constexpr int kBarFull = 0, kBarEmpty = 4, kBarImg = 8, kBarX = 12, kBarPrep = 15, kNumBars = 16;

constexpr uint32_t kSpinLimit = 1u << 24;

struct Scratch {
  uint16_t img[kImgBytes / 2];
  float dnn[kB * kSlots];
  unsigned int cnt[4];
};
__device__ __align__(1024) Scratch g_scratch;

#define PROF(slot) do {} while (0)
#define PROFG(slot) do {} while (0)
#define PROFU(slot) do {} while (0)
#define PROF_BEGIN() do {} while (0)
#define PROF_END() do {} while (0)

__host__ __device__ constexpr int xrow(int q, int u, int e) {
  int p = (q == 0) ? u : (q == 1) ? 12 - u : (q == 2) ? (2 * u + 7) % 13 : (2 * (12 - u) + 7) % 13;
  int s = ((q & 1) && (u == 0 || u == 1 || u == 4)) ? 1 : 0;
  return 2 * p + (e ^ s);
}
__host__ __device__ constexpr int feat(int q, int s) { return s < 6 ? 6 * q + s : 24 + (q >> 1); }
__host__ __device__ constexpr int lq(int i) {
  constexpr int L[13] = {0, 1, 4, 6, 2, 3, 5, 7, 8, 9, 10, 11, 12};
  return L[i];
}
__host__ __device__ constexpr int regU(int t) {
  constexpr int U[21] = {0, 0, 0, 0, 0, 1, 1, 1, 1, 2, 2, 2, 3, 3, 3, 4, 4, 5, 0, 1, 4};
  return t < 36 ? U[t >> 1] : U[t - 18];
}
__host__ __device__ constexpr int regV(int t) {
  constexpr int V[21] = {1, 3, 4, 9, 10, 2, 4, 5, 10, 3, 5, 6, 4, 6, 7, 5, 7, 6, 12, 11, 8};
  return t < 36 ? V[t >> 1] : V[t - 18];
}
__host__ __device__ constexpr int xpos(int j) {
  constexpr int P[27] = {8, 18, 16, 6, 19, 4, 1, 5, 14, 23, 17, 3, 10, 0, 20, 13, 24, 2, 12, 11, 21, 25, 15, 26, 22, 7, 9};
  return P[j];
}
__host__ __device__ constexpr int spec(int i) {
  constexpr int S[80] = {13, 13, 23, 22, 23, 23, 8,  8,  4,  4,  20, 20, 21, 21, 9,  8,  18, 18, 18, 19,
                         22, 22, 26, 26, 15, 15, 12, 13, 16, 17, 19, 19, 7,  6,  0,  0,  1,  0,  5,  5,
                         1,  1,  21, 20, 5,  4,  9,  9,  6,  6,  14, 15, 17, 17, 24, 24, 16, 16, 24, 25,
                         11, 11, 25, 25, 3,  2,  3,  3,  12, 12, 2,  2,  14, 14, 7,  7,  10, 10, 11, 10};
  return S[i];
}
struct Tables {
  uint32_t ldsm[32][4];
  uint16_t sent[384];
  uint32_t rowoff[16];
  uint32_t jrow[13][2];
};
constexpr Tables make_tables() {
  Tables t = {};
  for (int lane = 0; lane < 32; lane++) {
    int m = lane >> 3, q = (lane & 7) >> 1, e = lane & 1;
    for (int i = 0; i < 12; i++) {
      int r = i < 7 ? xrow(q, lq(i < 6 ? 2 * i + (m >> 1) : 12), e) : spec((i - 7) * 16 + q * 4 + e * 2 + (m >> 1));
      t.ldsm[lane][i >> 2] |= (uint32_t)(xpos(r) * 9 + (m & 1)) << (8 * (i & 3));
    }
    if (lane < 16) t.rowoff[lane] = (uint32_t)(xpos(lane) * kXPitch) | (uint32_t)(lane < 10 ? xpos(lane + 16) * kXPitch : 0) << 16;
  }
  for (int i = 0; i < 384; i++) {
    int slot = 2 * (i >> 4) + ((i >> 3) & 1) - 4, q = (i & 7) >> 1, e = i & 1, a = 0, b = 0;
    if (slot < 0) {
      const bool dup = slot == -1 && q > 0;
      a = dup ? 27 : xrow(q, lq(slot + 4), e);
      b = dup ? 27 : 26;
    } else if (slot < 39) {
      a = xrow(q, regU(slot), slot < 36 ? (slot & 1) : e);
      b = xrow(q, regV(slot), e);
    } else {
      a = spec((slot - 39) * 16 + q * 4 + e * 2);
      b = spec((slot - 39) * 16 + q * 4 + e * 2 + 1);
    }
    t.sent[i] = (uint16_t)(a <= b ? a | b << 8 : b | a << 8);
  }
  for (int u = 0; u < 13; u++)
    for (int k = 0; k < 8; k++) t.jrow[u][k >> 2] |= (uint32_t)xrow(k >> 1, u, k & 1) << (8 * (k & 3));
  return t;
}
__device__ const __align__(16) Tables g_tab = make_tables();

template <int I, int N, class Fn>
__device__ __forceinline__ void static_for(Fn&& f) {
  if constexpr (I < N) {
    f(std::integral_constant<int, I>{});
    static_for<I + 1, N>(f);
  }
}

__device__ __forceinline__ void mbar_init(uint32_t bar, uint32_t count) {
  asm volatile("mbarrier.init.shared::cta.b64 [%0], %1;" ::"r"(bar), "r"(count) : "memory");
}
__device__ __forceinline__ void mbar_expect_tx(uint32_t bar, uint32_t bytes) {
  asm volatile("mbarrier.arrive.expect_tx.shared::cta.b64 _, [%0], %1;" ::"r"(bar), "r"(bytes) : "memory");
}
__device__ __forceinline__ void mbar_arrive_cluster(uint32_t bar, uint32_t cta) {
  asm volatile(
      "{\n.reg .b32 ra;\nmapa.shared::cluster.u32 ra, %0, %1;\n"
      "mbarrier.arrive.shared::cluster.b64 _, [ra];\n}" ::"r"(bar), "r"(cta) : "memory");
}
__device__ __forceinline__ uint32_t mbar_try(uint32_t bar, uint32_t parity) {
  uint32_t ok;
  asm volatile(
      "{\n.reg .pred p;\nmbarrier.try_wait.parity.shared::cta.b64 p, [%1], %2;\nselp.u32 %0, 1, 0, p;\n}"
      : "=r"(ok) : "r"(bar), "r"(parity) : "memory");
  return ok;
}
__device__ __forceinline__ void mbar_wait(uint32_t bar, uint32_t parity) {
  uint32_t n = 0;
  while (!mbar_try(bar, parity)) {
    if (++n > kSpinLimit) __trap();
  }
}
__device__ __forceinline__ void wait_counter(const unsigned int* p, unsigned int target) {
  uint32_t n = 0, v;
  while (true) {
    asm volatile("ld.acquire.gpu.global.u32 %0, [%1];" : "=r"(v) : "l"(p) : "memory");
    if (v >= target) break;
    if (++n > (1u << 22)) __trap();
    __nanosleep(20);
  }
}
__device__ __forceinline__ void red_release(unsigned int* p) {
  asm volatile("red.release.gpu.global.add.u32 [%0], 1;" ::"l"(p) : "memory");
}
__device__ __forceinline__ void bulk_load(uint32_t dst, const void* src, uint32_t bytes, uint32_t bar) {
  asm volatile("cp.async.bulk.shared::cluster.global.mbarrier::complete_tx::bytes [%0], [%1], %2, [%3];"
               ::"r"(dst), "l"(src), "r"(bytes), "r"(bar) : "memory");
}
__device__ __forceinline__ void tma_load_mc(uint32_t dst, const CUtensorMap* map, int c0, int c1, uint32_t bar) {
  asm volatile(
      "cp.async.bulk.tensor.2d.shared::cluster.global.mbarrier::complete_tx::bytes.multicast::cluster"
      " [%0], [%1, {%3, %4}], [%2], %5;"
      ::"r"(dst), "l"(map), "r"(bar), "r"(c0), "r"(c1), "h"((uint16_t)3) : "memory");
}
__device__ __forceinline__ void cp_async16(uint32_t dst, const void* src) {
  asm volatile("cp.async.cg.shared.global [%0], [%1], 16;" ::"r"(dst), "l"(src) : "memory");
}
__device__ __forceinline__ void cp_async16_if(bool on, uint32_t dst, const void* src) {
  asm volatile("{.reg .pred p; setp.ne.u32 p, %2, 0; @p cp.async.cg.shared.global [%0], [%1], 16;}"
               ::"r"(dst), "l"(src), "r"((uint32_t)on) : "memory");
}
__device__ __forceinline__ void cp_async_arrive_if(bool on, uint32_t bar) {
  asm volatile("{.reg .pred p; setp.ne.u32 p, %1, 0; @p cp.async.mbarrier.arrive.noinc.shared::cta.b64 [%0];}"
               ::"r"(bar), "r"((uint32_t)on) : "memory");
}
__device__ __forceinline__ void cp_async_arrive(uint32_t bar) {
  asm volatile("cp.async.mbarrier.arrive.noinc.shared::cta.b64 [%0];" ::"r"(bar) : "memory");
}
__device__ __forceinline__ void fence_async_smem() { asm volatile("fence.proxy.async.shared::cta;" ::: "memory"); }
__device__ __forceinline__ void fence_async_global() { asm volatile("fence.proxy.async.global;" ::: "memory"); }
__device__ __forceinline__ void cp_async4(uint32_t dst, const void* src) {
  asm volatile("cp.async.ca.shared.global [%0], [%1], 4;" ::"r"(dst), "l"(src) : "memory");
}
__device__ __forceinline__ uint32_t ld_early16(const void* p) {
  uint32_t v;
  asm volatile("ld.global.nc.u16 %0, [%1];" : "=r"(v) : "l"(p));
  return v;
}
__device__ __forceinline__ uint32_t ld_early32(const void* p) {
  uint32_t v;
  asm volatile("ld.global.nc.u32 %0, [%1];" : "=r"(v) : "l"(p));
  return v;
}
__device__ __forceinline__ uint2 ld_early64(const void* p) {
  uint2 v;
  asm volatile("ld.global.nc.v2.u32 {%0,%1}, [%2];" : "=r"(v.x), "=r"(v.y) : "l"(p));
  return v;
}
__device__ __forceinline__ uint4 ld_early128(const void* p) {
  uint4 v;
  asm volatile("ld.global.nc.v4.u32 {%0,%1,%2,%3}, [%4];" : "=r"(v.x), "=r"(v.y), "=r"(v.z), "=r"(v.w) : "l"(p));
  return v;
}
__device__ __forceinline__ void cp_async_wait_all() { asm volatile("cp.async.wait_all;" ::: "memory"); }
__device__ __forceinline__ const uint8_t* row_ptr(const uint8_t* base, uint32_t row) {
  uint64_t p;
  asm("mad.wide.u32 %0, %1, 256, %2;" : "=l"(p) : "r"(row), "l"(base));
  return reinterpret_cast<const uint8_t*>(p);
}
template <int ID, int N>
__device__ __forceinline__ void bar_sync() { asm volatile("bar.sync %0, %1;" ::"n"(ID), "n"(N) : "memory"); }
template <int ID, int N>
__device__ __forceinline__ void bar_arrive() { asm volatile("bar.arrive %0, %1;" ::"n"(ID), "n"(N) : "memory"); }
__device__ __forceinline__ void wg_fence() { asm volatile("wgmma.fence.sync.aligned;" ::: "memory"); }
__device__ __forceinline__ void wg_commit() { asm volatile("wgmma.commit_group.sync.aligned;" ::: "memory"); }
template <int N>
__device__ __forceinline__ void wg_wait() { asm volatile("wgmma.wait_group.sync.aligned %0;" ::"n"(N) : "memory"); }
template <int N>
__device__ __forceinline__ void pin(float (&d)[N]) {
#pragma unroll
  for (int i = 0; i < N; i++) asm volatile("" : "+f"(d[i])::"memory");
}
__device__ __forceinline__ void ldsm4(uint32_t& r0, uint32_t& r1, uint32_t& r2, uint32_t& r3, uint32_t addr) {
  asm volatile("ldmatrix.sync.aligned.m8n8.x4.trans.shared.b16 {%0,%1,%2,%3}, [%4];"
               : "=r"(r0), "=r"(r1), "=r"(r2), "=r"(r3) : "r"(addr) : "memory");
}
__device__ __forceinline__ void ldsm2(uint32_t& r0, uint32_t& r1, uint32_t addr) {
  asm volatile("ldmatrix.sync.aligned.m8n8.x2.trans.shared.b16 {%0,%1}, [%2];" : "=r"(r0), "=r"(r1) : "r"(addr) : "memory");
}
__device__ __forceinline__ uint32_t mul2(uint32_t a, uint32_t b) {
  uint32_t r;
  asm("mul.rn.bf16x2 %0, %1, %2;" : "=r"(r) : "r"(a), "r"(b));
  return r;
}
template <int HI>
__device__ __forceinline__ uint32_t mul_dup(uint32_t a, uint32_t b) {
  uint32_t r;
  if constexpr (HI)
    asm("{.reg .b16 l,h; .reg .b32 t; mov.b32 {l,h}, %1; mov.b32 t, {h,h}; mul.rn.bf16x2 %0, t, %2;}" : "=r"(r) : "r"(a), "r"(b));
  else
    asm("{.reg .b16 l,h; .reg .b32 t; mov.b32 {l,h}, %1; mov.b32 t, {l,l}; mul.rn.bf16x2 %0, t, %2;}" : "=r"(r) : "r"(a), "r"(b));
  return r;
}
__device__ __forceinline__ uint32_t pack2(float lo, float hi) {
  uint32_t r;
  asm("cvt.rn.bf16x2.f32 %0, %1, %2;" : "=r"(r) : "f"(hi), "f"(lo));
  return r;
}
__device__ __forceinline__ float bf2f(uint16_t v) { return __uint_as_float((uint32_t)v << 16); }
__device__ __forceinline__ uint16_t f2bf(float v) { return __bfloat16_as_ushort(__float2bfloat16_rn(v)); }

template <int ACC>
__device__ __forceinline__ void wgmma_rs32(float (&d)[16], const uint32_t (&a)[4], uint64_t desc) {
  asm volatile(
      "wgmma.mma_async.sync.aligned.m64n32k16.f32.bf16.bf16 "
      "{%0,%1,%2,%3,%4,%5,%6,%7,%8,%9,%10,%11,%12,%13,%14,%15}, {%16,%17,%18,%19}, %20, %21, 1, 1, 0;"
      : "+f"(d[0]), "+f"(d[1]), "+f"(d[2]), "+f"(d[3]), "+f"(d[4]), "+f"(d[5]), "+f"(d[6]), "+f"(d[7]), "+f"(d[8]),
        "+f"(d[9]), "+f"(d[10]), "+f"(d[11]), "+f"(d[12]), "+f"(d[13]), "+f"(d[14]), "+f"(d[15])
      : "r"(a[0]), "r"(a[1]), "r"(a[2]), "r"(a[3]), "l"(desc), "n"(ACC));
}
template <int ACC>
__device__ __forceinline__ void wgmma_rs56(float (&d)[28], const uint32_t (&a)[4], uint64_t desc) {
  asm volatile(
      "wgmma.mma_async.sync.aligned.m64n56k16.f32.bf16.bf16 "
      "{%0,%1,%2,%3,%4,%5,%6,%7,%8,%9,%10,%11,%12,%13,%14,%15,%16,%17,%18,%19,%20,%21,%22,%23,%24,%25,%26,%27}, "
      "{%28,%29,%30,%31}, %32, %33, 1, 1, 0;"
      : "+f"(d[0]), "+f"(d[1]), "+f"(d[2]), "+f"(d[3]), "+f"(d[4]), "+f"(d[5]), "+f"(d[6]), "+f"(d[7]), "+f"(d[8]),
        "+f"(d[9]), "+f"(d[10]), "+f"(d[11]), "+f"(d[12]), "+f"(d[13]), "+f"(d[14]), "+f"(d[15]), "+f"(d[16]),
        "+f"(d[17]), "+f"(d[18]), "+f"(d[19]), "+f"(d[20]), "+f"(d[21]), "+f"(d[22]), "+f"(d[23]), "+f"(d[24]),
        "+f"(d[25]), "+f"(d[26]), "+f"(d[27])
      : "r"(a[0]), "r"(a[1]), "r"(a[2]), "r"(a[3]), "l"(desc), "n"(ACC));
}
#define XD_ACC8(o) "+f"(d[o]), "+f"(d[o + 1]), "+f"(d[o + 2]), "+f"(d[o + 3]), "+f"(d[o + 4]), "+f"(d[o + 5]), "+f"(d[o + 6]), "+f"(d[o + 7])
__device__ __forceinline__ void wgmma_ss256(float (&d)[128], uint64_t da, uint64_t db) {
  asm volatile(
      "wgmma.mma_async.sync.aligned.m64n256k16.f32.bf16.bf16 "
      "{%0,%1,%2,%3,%4,%5,%6,%7,%8,%9,%10,%11,%12,%13,%14,%15,%16,%17,%18,%19,%20,%21,%22,%23,%24,%25,%26,%27,%28,%29,%30,%31,"
      "%32,%33,%34,%35,%36,%37,%38,%39,%40,%41,%42,%43,%44,%45,%46,%47,%48,%49,%50,%51,%52,%53,%54,%55,%56,%57,%58,%59,%60,%61,%62,%63,"
      "%64,%65,%66,%67,%68,%69,%70,%71,%72,%73,%74,%75,%76,%77,%78,%79,%80,%81,%82,%83,%84,%85,%86,%87,%88,%89,%90,%91,%92,%93,%94,%95,"
      "%96,%97,%98,%99,%100,%101,%102,%103,%104,%105,%106,%107,%108,%109,%110,%111,%112,%113,%114,%115,%116,%117,%118,%119,%120,%121,%122,%123,%124,%125,%126,%127}, "
      "%128, %129, 1, 1, 1, 0, 1;"
      : XD_ACC8(0), XD_ACC8(8), XD_ACC8(16), XD_ACC8(24), XD_ACC8(32), XD_ACC8(40), XD_ACC8(48), XD_ACC8(56),
        XD_ACC8(64), XD_ACC8(72), XD_ACC8(80), XD_ACC8(88), XD_ACC8(96), XD_ACC8(104), XD_ACC8(112), XD_ACC8(120)
      : "l"(da), "l"(db));
}
__device__ __forceinline__ uint64_t make_desc(uint32_t addr, uint32_t lbo, uint32_t sbo, uint64_t swz) {
  return (uint64_t)((addr & 0x3FFFF) >> 4) | ((uint64_t)(lbo >> 4) << 16) | ((uint64_t)(sbo >> 4) << 32) | (swz << 62);
}

constexpr int kLayer = 26 * 26 * 26;
constexpr int kPrepW5 = 0, kPrepRow = 35200, kPrepCol = kPrepRow + 3 * 1376, kPrepW = kPrepCol + 3 * 2080;
constexpr int kPrepV = kPrepW + 320, kPrepP = kPrepV + 26 * 28 * 4;

__device__ __forceinline__ void stage_weights(int c, uint32_t sbase, const uint16_t* __restrict__ W,
                                              const uint16_t* __restrict__ wout) {
  const int tid = threadIdx.x, cf = feat(c / 7, c % 7);
  const uint8_t* Wb = reinterpret_cast<const uint8_t*>(W);
  {
    const int sl = tid >> 7, lay = sl == 0 ? 4 : sl == 1 ? 3 : 1;
#pragma unroll
    for (int r = 0; r < 2; r++) {
      const int ch = (tid & 127) + 128 * r, h = ch / 5;
      if (ch < 130)
        cp_async16(sbase + kPrepCol + sl * 2080 + ch * 16, Wb + lay * kLayer * 2 + ((h * 1352 + cf * 52) & ~15) + (ch - 5 * h) * 16);
    }
  }
  if (tid < 258) {
    const int sl = tid / 86, lay = sl == 0 ? 1 : sl == 1 ? 2 : 0;
    cp_async16(sbase + kPrepRow + tid * 16, Wb + lay * kLayer * 2 + ((cf * 1352) & ~15) + (tid - 86 * sl) * 16);
  } else if (tid >= 288 && tid < 288 + 39) {
    asm volatile("cp.async.ca.shared.global [%0], [%1], 8;" ::"r"(sbase + kPrepW + (tid - 288) * 8), "l"(wout + 4 * (tid - 288)) : "memory");
  }
}
__device__ __forceinline__ const uint16_t* rowslab(const uint8_t* smem, int sl, int cf) {
  return reinterpret_cast<const uint16_t*>(smem + kPrepRow + sl * 1376 + (cf & 1) * 8);
}
__device__ __forceinline__ const uint16_t* colslab(const uint8_t* smem, int sl, int cf, int h) {
  return reinterpret_cast<const uint16_t*>(smem + kPrepCol + sl * 2080 + h * 80 + ((h * 8 + cf * 52) & 15));
}

__device__ __forceinline__ void copy_item(int item, int cq, int cs, const uint8_t* smem, uint8_t* imgb, uint2 jr) {
  const int lay = item / 86, slot = item - 86 * lay, s = slot < 78 ? slot / 13 : 6, cf = feat(cq, cs);
  uint32_t v[8];
#pragma unroll
  for (int q = 0; q < 4; q++) {
    const int fi = feat(q, s);
    const uint16_t* src = lay == 1 ? colslab(smem, 1, cf, fi) : rowslab(smem, lay >> 1, cf) + fi * 26;
#pragma unroll
    for (int e = 0; e < 2; e++) {
      v[2 * q + e] = src[((q < 2 ? jr.x : jr.y) >> (8 * (2 * (q & 1) + e))) & 255];
      if (slot == 85 || (slot == 84 && (q & 1))) v[2 * q + e] = 0;
    }
  }
  if (slot == 85 && lay == 1) v[0] = reinterpret_cast<const uint16_t*>(smem + kPrepW)[2 * 26 + cf];
  uint4 o = make_uint4(v[0] | (v[1] << 16), v[2] | (v[3] << 16), v[4] | (v[5] << 16), v[6] | (v[7] << 16));
  if (lay != 0 && cs == 6 && (cq & 1)) o = make_uint4(0, 0, 0, 0);
  *reinterpret_cast<uint4*>(imgb + kImgF2 + lay * kImgLBytes + (slot >> 1) * 1024 + (cs >> 1) * 256 + (slot & 1) * 128 +
                            (2 * cq + (cs & 1)) * 16) = o;
}
__device__ __forceinline__ uint2 item_rows(const Tables* tab, int item) {
  const int slot = item % 86;
  return ld_early64(tab->jrow[slot >= 78 ? min(slot - 78, 6) : slot % 13]);
}

__device__ __forceinline__ void build_image(int c, uint8_t* smem, uint16_t* __restrict__ img, uint32_t ab, uint2 jr) {
  const uint16_t* sw = reinterpret_cast<const uint16_t*>(smem + kPrepW);
  float* sV = reinterpret_cast<float*>(smem + kPrepV);
  float* sP = reinterpret_cast<float*>(smem + kPrepP);
  const int tid = threadIdx.x, half = (tid >> 4) & 1, u16 = (tid >> 5) * 16 + (tid & 15);
  const int cq = c / 7, cs = c - 7 * cq, cf = feat(cq, cs);
  {
    const uint2* p = reinterpret_cast<const uint2*>(smem + kPrepW5) + min(u16, 168) + half * 13 * 169;
    const uint16_t* w5 = sw + 5 * 26 + half * 13;
    float v0 = 0.f, v1 = 0.f, v2 = 0.f, v3 = 0.f;
#pragma unroll
    for (int g = 0; g < 13; g++) {
      const uint2 w = p[g * 169];
      const float s = bf2f(w5[g]);
      v0 = fmaf(s, __uint_as_float(w.x << 16), v0);
      v1 = fmaf(s, __uint_as_float(w.x & 0xffff0000u), v1);
      v2 = fmaf(s, __uint_as_float(w.y << 16), v2);
      v3 = fmaf(s, __uint_as_float(w.y & 0xffff0000u), v3);
    }
    const float o0 = __shfl_xor_sync(0xffffffffu, half ? v0 : v2, 16), o1 = __shfl_xor_sync(0xffffffffu, half ? v1 : v3, 16);
    const int w = 2 * u16 + half;
    if (u16 < 169) *reinterpret_cast<float2*>(sV + 2 * w + 2 * (w / 13)) = make_float2((half ? v2 : v0) + o0, (half ? v3 : v1) + o1);
    if (tid >= 352 && tid < 378) *reinterpret_cast<float2*>(sV + (tid - 352) * 28 + 26) = make_float2(bf2f(sw[4 * 26 + tid - 352]), 0.f);
  }
  PROF(43 + (tid >> 7));
  __syncthreads();
  {
    const int un = min(u16, 181), pa = un / 14, pb = un - 14 * pa;
    const float2* vp = reinterpret_cast<const float2*>(sV) + pb + half * 13 * 14;
    float r0 = 0.f, r1 = 0.f, r2 = 0.f, r3 = 0.f;
#pragma unroll
    for (int h = 0; h < 13; h++) {
      const uint32_t w = reinterpret_cast<const uint32_t*>(colslab(smem, 0, cf, half * 13 + h))[pa];
      const float2 v = vp[h * 14];
      const float wl = __uint_as_float(w << 16), wh = __uint_as_float(w & 0xffff0000u);
      r0 = fmaf(wl, v.x, r0);
      r1 = fmaf(wl, v.y, r1);
      r2 = fmaf(wh, v.x, r2);
      r3 = fmaf(wh, v.y, r3);
    }
    const float o0 = __shfl_xor_sync(0xffffffffu, half ? r0 : r2, 16), o1 = __shfl_xor_sync(0xffffffffu, half ? r1 : r3, 16);
    if (u16 < 182) reinterpret_cast<float2*>(sP)[pa * 28 + half * 14 + pb] = make_float2((half ? r2 : r0) + o0, (half ? r3 : r1) + o1);
  }
  PROF(49 + (tid >> 7));
  __syncthreads();
  const int a = ab & 255, b = ab >> 8;
  const uint16_t* sX = rowslab(smem, 2, cf);
  float x1w = 0.f, g4w = 0.f;
  if (b < 26) x1w = a == b ? bf2f(sX[a * 27]) : bf2f(sX[a * 26 + b]) + bf2f(sX[b * 26 + a]);
  if (a == 26) g4w = bf2f(sw[3 * 26 + cf]);
  else if (a < 26) g4w = (b < 26 && a != b) ? sP[a * 28 + b] + sP[b * 28 + a] : sP[a * 28 + b];
  const int s4 = cs + 7, base = (tid >> 4) * 896 + ((tid >> 3) & 1) * 64 + (tid & 7);
  img[base + (cs >> 1) * 128 + (2 * cq + (cs & 1)) * 8] = f2bf(x1w);
  img[base + (s4 >> 1) * 128 + (2 * cq + (s4 & 1)) * 8] = f2bf(g4w);
  PROF(52 + (tid >> 7));
}

__device__ __forceinline__ void build_full_stages(int c, uint8_t* smem, uint16_t* __restrict__ img, uint2 jr) {
  const uint16_t* sw = reinterpret_cast<const uint16_t*>(smem + kPrepW);
  uint8_t* imgb = reinterpret_cast<uint8_t*>(img);
  const int tid = threadIdx.x;
  const int cq = c / 7, cs = c - 7 * cq, cf = feat(cq, cs);
  if (tid < 258) {
    copy_item(tid, cq, cs, smem, imgb, jr);
  } else if (tid >= 288 && tid < 288 + 34) {
    const int i = c * 34 + tid - 288;
    if (i < 11 * 86) {
      const int col = i / 86 + 1, slot = i % 86;
      *reinterpret_cast<uint4*>(imgb + kImgF2 + (col >> 2) * kImgLBytes + (slot >> 1) * 1024 + 3 * 256 + (slot & 1) * 128 +
                                (2 * (col & 3) + 1) * 16) = make_uint4(0, 0, 0, 0);
    }
  } else if (tid >= 352 && tid < 352 + 26) {
    const int u = (tid - 352) >> 1, e = tid & 1;
    if (cs < 6 || u < 8) {
      const int slot = cs < 6 ? cs * 13 + u : 78 + u;
      float v = 0.f;
      if (slot < 84 || (slot == 84 && !(cq & 1))) {
        const int j = ((cq < 2 ? jr.x : jr.y) >> (8 * (2 * (cq & 1) + e))) & 255;
#pragma unroll
        for (int h = 0; h < 26; h++) v = fmaf(bf2f(sw[26 + h]), bf2f(colslab(smem, 2, cf, h)[j]), v);
      }
      img[kImgF2 / 2 + (slot >> 1) * 512 + 3 * 128 + (slot & 1) * 64 + 8 + 2 * cq + e] = f2bf(v);
    }
  }
}

#define XD_GROUP 2
constexpr int kGroup = XD_GROUP;

template <int T>
__device__ __forceinline__ void slot_full(uint32_t& r0, uint32_t& r1, const uint32_t (&x)[2][13], const uint32_t (&y)[7]) {
  if constexpr (T >= 85) {
    r0 = 0x00003F80u;
    r1 = 0x00003F80u;
  } else {
    constexpr int s = T < 78 ? T / 13 : 6, u = T < 78 ? T % 13 : T - 78;
    r0 = mul_dup<0>(y[s], x[0][u]);
    r1 = mul_dup<1>(y[s], x[1][u]);
  }
}

template <class Late>
__device__ __forceinline__ void full_stage(float (&acc)[16], const uint32_t (&x)[2][13], const uint32_t (&y)[7], uint64_t desc,
                                           Late&& late) {
  static_for<0, (kStepsL + kGroup - 1) / kGroup>([&](auto gi) {
    constexpr int t0 = decltype(gi)::value * kGroup;
    constexpr int n = (kStepsL - t0) < kGroup ? (kStepsL - t0) : kGroup;
    uint32_t a[n][4];
    static_for<0, n>([&](auto j) {
      constexpr int t = t0 + decltype(j)::value;
      slot_full<2 * t>(a[decltype(j)::value][0], a[decltype(j)::value][1], x, y);
      slot_full<2 * t + 1>(a[decltype(j)::value][2], a[decltype(j)::value][3], x, y);
    });
    wg_fence();
    static_for<0, n>([&](auto j) {
      constexpr int t = t0 + decltype(j)::value;
      wgmma_rs32<(t > 0)>(acc, a[decltype(j)::value], desc + (uint64_t)(t * 64));
    });
    wg_commit();
    wg_wait<1>();
    if constexpr (t0 == 16 * kGroup) late();
  });
}
template <int OFF, int N>
__device__ __forceinline__ void pack_slots(uint32_t (&y)[7], const float (&acc)[N]) {
#pragma unroll
  for (int s = 0; s < 7; s++) y[s] = pack2(acc[4 * ((s + OFF) >> 1) + ((s + OFF) & 1)], acc[4 * ((s + OFF) >> 1) + 2 + ((s + OFF) & 1)]);
}

__device__ __forceinline__ void tile_begin(uint32_t (&x)[2][13], float (&accS)[28], const uint32_t (&xa)[12], uint32_t xo,
                                           uint64_t dS) {
  static_for<0, 6>([&](auto ii) {
    constexpr int i = decltype(ii)::value;
    ldsm4(x[0][lq(2 * i)], x[1][lq(2 * i)], x[0][lq(2 * i + 1)], x[1][lq(2 * i + 1)], xa[i] + xo);
  });
  ldsm2(x[0][12], x[1][12], xa[6] + xo);
  const uint32_t l0[4] = {x[0][lq(0)], x[1][lq(0)], x[0][lq(1)], x[1][lq(1)]};
  const uint32_t l1[4] = {x[0][lq(2)], x[1][lq(2)], x[0][lq(3)], x[1][lq(3)]};
  wg_fence();
  wgmma_rs56<0>(accS, l0, dS);
  wgmma_rs56<1>(accS, l1, dS + 112);
  wg_commit();
  wg_wait<1>();
}

template <class Hook, class Hook2>
__device__ __forceinline__ void stage_s_rest(const uint32_t (&x)[2][13], float (&accS)[28], const uint32_t (&xa)[12], uint32_t xo,
                                             uint64_t dS, Hook&& hook, Hook2&& hook2) {
  uint32_t e[5][4];
  static_for<1, kStepsS / 2>([&](auto gi) {
    constexpr int t0 = decltype(gi)::value * 2;
    if constexpr (t0 == 18) ldsm4(e[0][0], e[0][1], e[0][2], e[0][3], xa[7] + xo);
    if constexpr (t0 == 20) {
#pragma unroll
      for (int i = 1; i < 5; i++) ldsm4(e[i][0], e[i][1], e[i][2], e[i][3], xa[7 + i] + xo);
    }
    uint32_t a[2][4];
    static_for<0, 4>([&](auto j) {
      constexpr int jj = decltype(j)::value, slot = 2 * t0 + jj - 4;
      uint32_t& r0 = a[jj >> 1][(jj & 1) * 2];
      uint32_t& r1 = a[jj >> 1][(jj & 1) * 2 + 1];
      if constexpr (slot < 36) {
        r0 = mul_dup<slot & 1>(x[0][regU(slot)], x[0][regV(slot)]);
        r1 = mul_dup<slot & 1>(x[1][regU(slot)], x[1][regV(slot)]);
      } else if constexpr (slot < 39) {
        r0 = mul2(x[0][regU(slot)], x[0][regV(slot)]);
        r1 = mul2(x[1][regU(slot)], x[1][regV(slot)]);
      } else {
        r0 = mul2(e[slot - 39][0], e[slot - 39][2]);
        r1 = mul2(e[slot - 39][1], e[slot - 39][3]);
      }
    });
    wg_fence();
    wgmma_rs56<1>(accS, a[0], dS + (uint64_t)(t0 * 112));
    wgmma_rs56<1>(accS, a[1], dS + (uint64_t)((t0 + 1) * 112));
    wg_commit();
    wg_wait<1>();
    if constexpr (t0 == 2) hook();
    if constexpr (t0 == 8) hook2();
  });
  wg_wait<0>();
  pin(accS);
}

template <class WaitX, class Prefetch, class Last, class Emit>
__device__ __forceinline__ void cin_loop(int n, const uint32_t (&xa)[12], uint32_t xbase, const float (&w0q)[7], uint32_t sbase,
                                         uint32_t imgbar, WaitX&& waitx, Prefetch&& prefetch, Last&& last, Emit&& emit) {
  uint64_t dS = make_desc(sbase, 128, 256, 0);
  uint32_t x[2][13];
  float accS[28];
  waitx(0);
  mbar_wait(imgbar, 0);
  tile_begin(x, accS, xa, xbase, dS);
  stage_s_rest(x, accS, xa, xbase, dS, [] {}, [&] { prefetch(0); });
  mbar_wait(imgbar + 8, 0);
#pragma unroll 1
  for (int it = 0;; it++) {
    const bool first = it == 0, more = it + 1 < n;
    dS += (uint32_t)it >> 30;
    uint32_t y1[7], y4[7];
    pack_slots<0>(y1, accS);
    pack_slots<7>(y4, accS);
    float sum0 = 0.f, sum1 = 0.f;
#pragma unroll
    for (int s = 0; s < 7; s++) {
      sum0 = fmaf(w0q[s], accS[4 * (s >> 1) + (s & 1)], sum0);
      sum1 = fmaf(w0q[s], accS[4 * (s >> 1) + 2 + (s & 1)], sum1);
    }
    float accA[16], accG[16], accX[16];
    full_stage(accA, x, y1, dS + (uint64_t)(kImgF2 >> 4), [&] { if (first) mbar_wait(imgbar + 16, 0); });
    full_stage(accG, x, y4, dS + (uint64_t)(kImgB3 >> 4), [&] { if (first) mbar_wait(imgbar + 24, 0); });
    pin(accA);
    uint32_t y2[7];
    pack_slots<0>(y2, accA);
    sum0 += accA[13];
    sum1 += accA[15];
    full_stage(accX, x, y2, dS + (uint64_t)(kImgF3 >> 4), [&] { if (more) waitx(it + 1); else last(); });
    auto finish = [&] {
      pin(accG);
      pin(accX);
#pragma unroll
      for (int s = 0; s < 7; s++) {
        sum0 = fmaf(accG[4 * (s >> 1) + (s & 1)], accX[4 * (s >> 1) + (s & 1)], sum0);
        sum1 = fmaf(accG[4 * (s >> 1) + 2 + (s & 1)], accX[4 * (s >> 1) + 2 + (s & 1)], sum1);
      }
      emit(it, sum0 + sum1);
    };
    if (!more) {
      wg_wait<0>();
      finish();
      break;
    }
    const uint32_t xo = xbase + ((it + 1) & 1) * kXBufBytes;
    tile_begin(x, accS, xa, xo, dS);
    stage_s_rest(x, accS, xa, xo, dS, finish, [&] { prefetch(it + 1); });
  }
}

__device__ __forceinline__ void x_prefetch(bool on, uint32_t sbase, const uint32_t* s_idx, const uint8_t* table, uint32_t rowoff,
                                           int tile, int wg, int par) {
  const int t = threadIdx.x & 127, r = t >> 3;
  const uint32_t* ip = s_idx + (tile >> 1) * kF + r;
  const uint32_t dst = sbase + kOffX + (2 * wg + par) * kXBufBytes + (t & 7) * 16;
  const uint8_t* src = table + (tile & 1) * 128 + (t & 7) * 16;
  const uint32_t r0 = ip[0], r1 = ip[16];
  cp_async16_if(on, dst + (rowoff & 0xffffu), row_ptr(src, r0));
  cp_async16_if(on && r < kF - 16, dst + (rowoff >> 16), row_ptr(src, r1));
  cp_async_arrive_if(on, sbase + kOffBar + 8 * (kBarX + wg));
}

__device__ __forceinline__ void ones_rows(uint8_t* smem, int t) {
  if (t < 48)
    *reinterpret_cast<uint4*>(smem + kOffX + (t >> 3) * kXBufBytes + xpos(26) * kXPitch + (t & 7) * 16) =
        make_uint4(0x3F803F80u, 0x3F803F80u, 0x3F803F80u, 0x3F803F80u);
}

__device__ __forceinline__ void publish(float* slot, float v) {
  uint32_t bits = __float_as_uint(v);
  if (bits == 0) bits = 0x80000000u;
  asm volatile("st.relaxed.gpu.global.u32 [%0], %1;" ::"l"(slot), "r"(bits) : "memory");
}

__device__ __forceinline__ void await_image(Scratch* scr) {
  wait_counter(&scr->cnt[0], kPrepCtas);
  wait_counter(&scr->cnt[2], kPrepCtas);
  fence_async_global();
}
__device__ __forceinline__ void ack_image(Scratch* scr) {
  if (atomicAdd(&scr->cnt[1], 1u) == kCtas - 1) {
    scr->cnt[0] = 0;
    scr->cnt[1] = 0;
    scr->cnt[2] = 0;
  }
}
__device__ __forceinline__ void load_image_part(uint32_t sbase, const Scratch* scr, int p) {
  const uint32_t off = p == 0 ? 0 : kImgF2 + (p - 1) * kImgLBytes, bytes = p == 0 ? kImgSBytes : kImgLBytes;
  const uint32_t bar = sbase + kOffBar + 8 * (kBarImg + p);
  mbar_expect_tx(bar, bytes);
  bulk_load(sbase + off, reinterpret_cast<const uint8_t*>(scr->img) + off, bytes, bar);
}

__global__ void __cluster_dims__(2, 1, 1) __launch_bounds__(kThreads, 1)
xdeepfm_kernel(const __grid_constant__ CUtensorMap tmW, const int* __restrict__ idx, const uint8_t* __restrict__ table,
               const uint16_t* __restrict__ wcin, const uint16_t* __restrict__ wout, const uint16_t* __restrict__ b1,
               const uint16_t* __restrict__ w2, const uint16_t* __restrict__ bout, uint16_t* __restrict__ out,
               Scratch* scr, const Tables* __restrict__ tab) {
  extern __shared__ uint8_t smem_raw[];
  const uint32_t raw = (uint32_t)__cvta_generic_to_shared(smem_raw);
  const uint32_t sbase = (raw + 1023u) & ~1023u;
  uint8_t* smem = smem_raw + (sbase - raw);
  const int tid = threadIdx.x, lane = tid & 31;
  const int wg = __shfl_sync(0xffffffffu, tid >> 7, 0);
  const int warp = __shfl_sync(0xffffffffu, (tid >> 5) & 3, 0);
  const int cta = blockIdx.x;
  const bool gemm = cta >= kPrepCtas;
  const uint32_t bars = sbase + kOffBar;
  uint32_t* s_idx = reinterpret_cast<uint32_t*>(smem + kOffIdx);

  const int g = cta - kPrepCtas;
  const int tile0 = gemm ? kPrepTilesTotal + g * kGemmTiles : cta * kPrepBase + min(cta, kPrepRem);
  const int ntile = gemm ? kGemmTiles : kPrepBase + (cta < kPrepRem ? 1 : 0);
  const int toff = tile0 & 1, samp0 = tile0 >> 1, nsamp = (toff + ntile + 1) >> 1;
  const int pair = g >> 1, rank = cta & 1;
  const int nt = pair % kNTiles, m0 = (2 * (pair / kNTiles) + rank) * 128;

  PROF_BEGIN();
  PROFG(30);
  uint32_t rowoff, xa[12];
  float w0q[7], bias;
  uint4 t4;
  uint32_t w0raw[4], braw;
  auto load_cin_consts = [&]() {
    rowoff = ld_early32(&tab->rowoff[(tid & 127) >> 3]);
    t4 = ld_early128(tab->ldsm[lane]);
    const uint32_t* wp = reinterpret_cast<const uint32_t*>(wout);
#pragma unroll
    for (int i = 0; i < 3; i++) w0raw[i] = ld_early32(wp + 3 * (lane & 3) + i);
    w0raw[3] = ld_early32(wp + 12);
    braw = ld_early16(bout);
  };
  auto expand_cin_consts = [&]() {
#pragma unroll
    for (int i = 0; i < 12; i++) xa[i] = (((i < 4 ? t4.x : i < 8 ? t4.y : t4.z) >> (8 * (i & 3))) & 255) * 16 + (tid & 96);
#pragma unroll
    for (int s = 0; s < 6; s++) w0q[s] = __uint_as_float((s & 1) ? w0raw[s >> 1] & 0xffff0000u : w0raw[s >> 1] << 16);
    w0q[6] = (lane & 1) ? 0.f : __uint_as_float((lane & 2) ? w0raw[3] & 0xffff0000u : w0raw[3] << 16);
    bias = __uint_as_float(braw << 16);
  };

  auto init_barriers = [&]() {
#pragma unroll
    for (int i = 0; i < kNumBars; i++) mbar_init(bars + 8 * i, i < kBarEmpty ? 129 : i < kBarImg ? 4 : (i < kBarX || i == kBarPrep) ? 1 : 128);
    asm volatile("fence.mbarrier_init.release.cluster;" ::: "memory");
  };

  uint2 cur[8];
  const int* ip = idx + (m0 + ((tid & 127) >> 3)) * kF;
#pragma unroll
  for (int i = 0; i < 8; i++)
    asm volatile("{.reg .pred p; setp.ne.u32 p, %3, 0; mov.b32 %0, 0; mov.b32 %1, 0; @p ld.global.nc.v2.u32 {%0,%1}, [%2];}"
                 : "=r"(cur[i].x), "=r"(cur[i].y) : "l"(ip + 16 * i * kF), "r"((uint32_t)(gemm && tid < 128)));
  PROF(1);

  if (gemm) {
    if (tid == 128) init_barriers();
    if (tid == 96) asm volatile("prefetch.tensormap [%0];" ::"l"(&tmW) : "memory");
    __syncwarp();
    asm volatile("barrier.cluster.arrive.relaxed.aligned;\nbarrier.cluster.wait.aligned;" ::: "memory");
    PROF(23 + wg);
    if (wg == 0) {
      const uint32_t dst0 = sbase + (tid >> 3) * 128 + (((tid & 7) ^ ((tid >> 3) & 7)) << 4);
      const uint8_t* src0 = table + (tid & 7) * 16;
      uint32_t si0 = 0, si1 = 0;
      auto load_w = [&](int kb) {
        if (tid == 96) {
          const uint32_t full = bars + 8 * (kBarFull + (kb & 3));
          const uint32_t bd = sbase + (kb & 3) * kStageBytes + kABytes + rank * 16384;
          mbar_expect_tx(full, 32768);
          tma_load_mc(bd, &tmW, nt * 256 + rank * 128, kb * 64, full);
          tma_load_mc(bd + 8192, &tmW, nt * 256 + rank * 128 + 64, kb * 64, full);
        }
      };
#pragma unroll 1
      for (int f2 = 0; f2 < kF / 2; f2++) {
        const uint8_t* rp[8];
        uint32_t odd[8];
#pragma unroll
        for (int s = 0; s < kStages; s++) {
          const int kb = 4 * f2 + s;
          const uint32_t full = bars + 8 * (kBarFull + s);
          mbar_wait(bars + 8 * (kBarEmpty + s), (f2 & 1) ^ 1);
          if (f2 > 0 || s == 0) load_w(kb);
          if (s == 0) {
#pragma unroll
            for (int i = 0; i < 8; i++) {
              rp[i] = row_ptr(src0, cur[i].x);
              odd[i] = cur[i].y;
            }
            if (kb == 0) PROF(29);
          } else if (s == 2) {
#pragma unroll
            for (int i = 0; i < 8; i++) rp[i] = row_ptr(src0, odd[i]);
          }
#pragma unroll
          for (int i = 0; i < 8; i++) cp_async16(dst0 + s * kStageBytes + i * 2048, rp[i] + (s & 1) * 128);
          cp_async_arrive(full);
          if (s == 1) {
            const int fn = 2 * min(f2 + 1, kF / 2 - 1);
#pragma unroll
            for (int i = 0; i < 8; i++) cur[i] = ld_early64(ip + 16 * i * kF + fn);
          }
          if (kb == 0) PROF(26);
          if (kb == XD_B1) load_w(1);
        }
        if (f2 == 0) {
          PROF(27);
          mbar_wait(bars + 8 * kBarFull, 0);
          load_w(2);
          load_w(3);
        }
        if (f2 == 1) {
          load_cin_consts();
          si0 = ld_early32(idx + samp0 * kF + tid);
          if (tid + 128 < nsamp * kF) si1 = ld_early32(idx + samp0 * kF + tid + 128);
        } else if (f2 == 2) {
          static_assert(kGemmTiles / 2 * kF >= 128 && (kGemmTiles / 2 + 1) * kF <= 256, "two index words per producer thread");
          s_idx[tid] = si0;
          s_idx[tid + 128] = si1;
          ones_rows(smem, tid);
          bar_sync<1, 128>();
          bar_arrive<2, 256>();
          bar_arrive<4, 256>();
#pragma unroll
          for (int w = 0; w < 3; w++) x_prefetch(true, sbase, s_idx, table, rowoff, toff + w, w, 0);
        } else if (f2 == 8 && tid == 0) {
          await_image(scr);
          ack_image(scr);
        }
      }
      PROF(3);
      expand_cin_consts();
#pragma unroll 1
      for (int p = 0; p < 4; p++) {
        mbar_wait(bars + 8 * (kBarEmpty + p), 0);
        if (tid == 0) load_image_part(sbase, scr, p);
      }
      PROF(4);
    } else {
      float acc[128];
      {
        const uint32_t* bp = reinterpret_cast<const uint32_t*>(b1 + nt * 256) + (lane & 3);
#pragma unroll
        for (int nb = 0; nb < 32; nb++) {
          const uint32_t b2 = ld_early32(bp + 4 * nb);
          acc[4 * nb] = acc[4 * nb + 2] = __uint_as_float(b2 << 16);
          acc[4 * nb + 1] = acc[4 * nb + 3] = __uint_as_float(b2 & 0xffff0000u);
        }
        if (wg == 1) {
          const uint32_t ww = ld_early32(reinterpret_cast<const uint32_t*>(w2 + nt * 256) + tid - 128);
          *reinterpret_cast<float2*>(smem + kOffEpi + (tid - 128) * 8) =
              make_float2(0.5f * __uint_as_float(ww << 16), 0.5f * __uint_as_float(ww & 0xffff0000u));
        }
        bar_sync<5, 256>();
        pin(acc);
      }
      const uint64_t dA = make_desc(sbase + (wg - 1) * 8192, 16, 1024, 1);
      const uint64_t dB = make_desc(sbase + kABytes, 8192, 1024, 1);
#pragma unroll 1
      for (int kb = 0; kb < kKBlocks; kb++) {
        const int s = kb & 3;
        mbar_wait(bars + 8 * (kBarFull + s), (kb >> 2) & 1);
        if (kb == 0) PROF(4 + wg);
        const bool held = kb == kKBlocks - kStages && wg == 2;
        if (held) {
          wg_wait<0>();
          if ((tid & 95) == 0) mbar_arrive_cluster(bars + 8 * (kBarEmpty + 3), (tid >> 5) & 1);
          bar_sync<3, 256>();
        }
        fence_async_smem();
        wg_fence();
        const uint64_t so = (uint64_t)(s * (kStageBytes >> 4));
#pragma unroll
        for (int k = 0; k < 4; k++) wgmma_ss256(acc, dA + so + k * 2, dB + so + k * 128);
        wg_commit();
        if (kb == kKBlocks - 1 && wg == 1) bar_arrive<3, 256>();
        wg_wait<1>();
        if (kb > 0 && !held && (tid & 95) == 0) mbar_arrive_cluster(bars + 8 * (kBarEmpty + ((kb - 1) & 3)), (tid >> 5) & 1);
      }
      wg_wait<0>();
      pin(acc);
      if ((tid & 95) == 0) mbar_arrive_cluster(bars + 8 * (kBarEmpty + 3), (tid >> 5) & 1);
      PROF(6 + wg);
      if (wg == 1) bar_sync<2, 256>(); else bar_sync<4, 256>();
      load_cin_consts();
      float r0 = 0.f, r1 = 0.f, r2 = 0.f, r3 = 0.f;
      const float2* epi = reinterpret_cast<const float2*>(smem + kOffEpi) + (lane & 3);
#pragma unroll
      for (int nb = 0; nb < 32; nb++) {
        const float2 e = epi[nb * 4];
        float gl[4];
#pragma unroll
        for (int j = 0; j < 4; j++) {
          const float v = acc[4 * nb + j];
          const float arg = v * fmaf(v * v, 0.0356774081f, 0.7978845608f);
          float t;
          asm("tanh.approx.f32 %0, %1;" : "=f"(t) : "f"(arg));
          gl[j] = fmaf(v, t, v);
        }
        r0 = fmaf(gl[0], e.x, r0);
        r2 = fmaf(gl[1], e.y, r2);
        r1 = fmaf(gl[2], e.x, r1);
        r3 = fmaf(gl[3], e.y, r3);
      }
      r0 += r2;
      r1 += r3;
      r0 += __shfl_xor_sync(0xffffffffu, r0, 1);
      r1 += __shfl_xor_sync(0xffffffffu, r1, 1);
      r0 += __shfl_xor_sync(0xffffffffu, r0, 2);
      r1 += __shfl_xor_sync(0xffffffffu, r1, 2);
      if ((lane & 3) < 2) {
        const int row = m0 + (wg - 1) * 64 + warp * 16 + (lane >> 2) + 8 * (lane & 1);
        publish(scr->dnn + row * kSlots + nt, (lane & 1) ? r1 : r0);
      }
      expand_cin_consts();
      PROF(8 + wg);
    }
    __syncwarp();
    asm volatile("barrier.cluster.arrive.relaxed.aligned;" ::: "memory");
  } else {
    if (tid == 352) {
      const uint8_t* w5 = reinterpret_cast<const uint8_t*>(wcin + 5 * kLayer);
      init_barriers();
      mbar_expect_tx(bars + 8 * kBarPrep, kLayer * 2);
      bulk_load(sbase + kPrepW5, w5, kLayer * 2, bars + 8 * kBarPrep);
    }
    __syncwarp();
    stage_weights(cta, sbase, wcin, wout);
    PROF(2);
    const uint32_t ab = ld_early16(&tab->sent[tid]);
    const uint2 jr = item_rows(tab, tid < 352 ? tid : (tid - 352) >> 1);
    load_cin_consts();
    uint32_t si0 = 0, si1 = 0;
    if (tid < nsamp * kF) si0 = ld_early32(idx + samp0 * kF + tid);
    if (tid + kThreads < nsamp * kF) si1 = ld_early32(idx + samp0 * kF + tid + kThreads);
    PROF(34 + wg);
    cp_async_wait_all();
    PROF(37 + wg);
    __syncthreads();
    mbar_wait(bars + 8 * kBarPrep, 0);
    PROF(40 + wg);
    build_image(cta, smem, scr->img, ab, jr);
    __syncthreads();
    PROF(3 + wg);
    if (tid == 320) red_release(&scr->cnt[0]);
    build_full_stages(cta, smem, scr->img, jr);
    s_idx[tid] = si0;
    if (tid + kThreads < kMaxSamples * kF) s_idx[tid + kThreads] = si1;
    ones_rows(smem, tid);
    __syncthreads();
    PROF(26 + wg);
    if (tid == 32) red_release(&scr->cnt[2]);
    if (tid == 256) {
      wait_counter(&scr->cnt[0], kPrepCtas);
      fence_async_global();
      PROF(6);
      fence_async_smem();
      load_image_part(sbase, scr, 0);
      await_image(scr);
      for (int p = 1; p < 4; p++) load_image_part(sbase, scr, p);
      PROF(7);
    }
    __syncwarp();
    x_prefetch(true, sbase, s_idx, table, rowoff, toff + wg, wg, 0);
    expand_cin_consts();
    if (tid == 256) ack_image(scr);
  }
  __syncwarp();

  {
    float* s_red = reinterpret_cast<float*>(smem + kOffRed) + (tid & 127);

    int wgu;
    asm volatile("shfl.sync.idx.b32 %0, %1, 0, 31, 0xffffffff;" : "=r"(wgu) : "r"(tid >> 7));
    PROF(11 + wg);
    cin_loop((ntile - wgu + 2) / 3, xa, sbase + kOffX + 2 * wgu * kXBufBytes, w0q, sbase, bars + 8 * kBarImg,
             [&](int it) { mbar_wait(bars + 8 * (kBarX + wgu), it & 1); },
             [&](int it) {
               const int tile = wgu + 3 * it;
               x_prefetch(tile + 3 < ntile, sbase, s_idx, table, rowoff, toff + tile + 3, wgu, (it + 1) & 1);
             },
             [&] { cp_async16_if(tid < 5 * nsamp, sbase + kOffDnn + tid * 16, scr->dnn + samp0 * kSlots + tid * 4); },
             [&](int it, float v) {
               const int tile = wgu + 3 * it;
               s_red[(toff + tile) * 128] = v;
               if (tile < toff) {
#pragma unroll
                 for (int o = 16; o > 0; o >>= 1) v += __shfl_xor_sync(0xffffffffu, v, o);
                 if (lane == 0) publish(scr->dnn + samp0 * kSlots + kNTiles + warp, v);
               }
               PROFU(90 + tile);
             });
  }
  PROF(17 + wg);
  cp_async_wait_all();
  __syncthreads();
  {
    float c[2];
#pragma unroll
    for (int r = 0; r < 2; r++) {
      const int sl = toff + (tid >> 5) + r * (kThreads / 32);
      c[r] = 0.f;
      if (sl < nsamp) {
        const bool whole = 2 * sl + 1 < toff + ntile;
        const float4* rp = reinterpret_cast<const float4*>(smem + kOffRed + sl * 1024) + lane;
        const float4 p0 = rp[0], p1 = whole ? rp[32] : make_float4(0.f, 0.f, 0.f, 0.f);
        float d = 0.f;
        if (lane < (whole ? kNTiles : kNTiles + 4)) {
          float* gp = scr->dnn + (samp0 + sl) * kSlots + lane;
          uint32_t bits = *reinterpret_cast<const uint32_t*>(smem + kOffDnn + sl * kSlots * 4 + lane * 4);
          for (uint32_t n = 0; bits == 0; n++) {
            asm volatile("ld.relaxed.gpu.global.u32 %0, [%1];" : "=r"(bits) : "l"(gp) : "memory");
            if (n > (1u << 22)) __trap();
          }
          d = __uint_as_float(bits);
          *gp = 0.f;
        }
        c[r] = (((p0.x + p0.y) + (p0.z + p0.w)) + ((p1.x + p1.y) + (p1.z + p1.w))) + d;
      }
    }
    __syncwarp();
#pragma unroll
    for (int o = 16; o > 0; o >>= 1) {
      c[0] += __shfl_xor_sync(0xffffffffu, c[0], o);
      c[1] += __shfl_xor_sync(0xffffffffu, c[1], o);
    }
    const int sl = toff + (tid >> 5) + lane * (kThreads / 32);
    if (lane < 2 && sl < nsamp) out[samp0 + sl] = f2bf((lane ? c[1] : c[0]) + bias);
    static_assert(kMaxSamples <= 2 * kThreads / 32, "two samples per warp");
  }
  PROF(20 + wg);
  PROFG(31);
  PROF_END();
  __syncwarp();
  if (gemm) asm volatile("barrier.cluster.wait.aligned;" ::: "memory");
}

typedef CUresult (*EncodeFn)(CUtensorMap*, CUtensorMapDataType, cuuint32_t, void*, const cuuint64_t*, const cuuint64_t*,
                             const cuuint32_t*, const cuuint32_t*, CUtensorMapInterleave, CUtensorMapSwizzle,
                             CUtensorMapL2promotion, CUtensorMapFloatOOBfill);

}

extern "C" void kernel_launch(void* const* d_in, const int* in_sizes, int n_in, void* d_out, int out_size) {
  (void)in_sizes; (void)n_in; (void)out_size;
  static EncodeFn encode = nullptr;
  static void* scr = nullptr;
  static void* tab = nullptr;
  if (!encode) {
    cudaGetSymbolAddress(&scr, g_scratch);
    cudaGetSymbolAddress(&tab, g_tab);
    void* fn = nullptr;
    cudaDriverEntryPointQueryResult st;
    cudaGetDriverEntryPoint("cuTensorMapEncodeTiled", &fn, cudaEnableDefault, &st);
    encode = reinterpret_cast<EncodeFn>(fn);
    cudaFuncSetAttribute(xdeepfm_kernel, cudaFuncAttributeMaxDynamicSharedMemorySize, kSmemBytes);
  }
  CUtensorMap tm;
  const cuuint64_t dims[2] = {(cuuint64_t)kDin, (cuuint64_t)kDin};
  const cuuint64_t strides[1] = {(cuuint64_t)kDin * 2};
  const cuuint32_t box[2] = {64, 64};
  const cuuint32_t estr[2] = {1, 1};
  encode(&tm, CU_TENSOR_MAP_DATA_TYPE_BFLOAT16, 2, d_in[4], dims, strides, box, estr, CU_TENSOR_MAP_INTERLEAVE_NONE,
         CU_TENSOR_MAP_SWIZZLE_128B, CU_TENSOR_MAP_L2_PROMOTION_L2_256B, CU_TENSOR_MAP_FLOAT_OOB_FILL_NONE);
  xdeepfm_kernel<<<kCtas, kThreads, kSmemBytes>>>(
      tm, (const int*)d_in[0], (const uint8_t*)d_in[1], (const uint16_t*)d_in[2], (const uint16_t*)d_in[3],
      (const uint16_t*)d_in[5], (const uint16_t*)d_in[6], (const uint16_t*)d_in[7], (uint16_t*)d_out,
      (Scratch*)scr, (const Tables*)tab);
}
```

```cpp
#include <cuda_runtime.h>
#include <cuda_bf16.h>
#include <cuda.h>
#include <stdint.h>
#include <type_traits>

namespace {

constexpr int kB = 1024, kF = 26, kDin = 3328;
constexpr int kCtas = 132, kPrepCtas = 28, kGemmCtas = 104, kThreads = 384;
constexpr int kStages = 4, kStageBytes = 49152, kABytes = 16384, kKBlocks = 52;
constexpr int kNTiles = 13;

constexpr int kStepsS = 24, kStepsL = 43;
constexpr int kImgSBytes = kStepsS * 56 * 32;
constexpr int kImgLBytes = kStepsL * 32 * 32;
constexpr int kImgF2 = kImgSBytes, kImgB3 = kImgF2 + kImgLBytes, kImgF3 = kImgB3 + kImgLBytes;
constexpr int kImgBytes = kImgF3 + kImgLBytes;

#define XD_GEMM_TILES 12
constexpr int kGemmTiles = XD_GEMM_TILES;
constexpr int kPrepTilesTotal = 2 * kB - kGemmCtas * kGemmTiles;
constexpr int kPrepBase = kPrepTilesTotal / kPrepCtas, kPrepRem = kPrepTilesTotal % kPrepCtas;
constexpr int kMaxSamples = 18, kSlots = 20;
static_assert(kPrepBase / 2 + 2 <= kMaxSamples && kGemmTiles / 2 + 1 <= kMaxSamples, "sample table too small");

constexpr int kXPitch = 144, kXBufBytes = 27 * kXPitch;
constexpr int kOffRed = kImgBytes;
constexpr int kOffX = kStages * kStageBytes;
constexpr int kOffEpi = kOffX + 6 * kXBufBytes;
constexpr int kOffIdx = kOffEpi + 2048;
constexpr int kOffDnn = kOffIdx + 2 * kMaxSamples * 128;
constexpr int kOffBar = kOffDnn + kMaxSamples * kSlots * 4;
constexpr int kSmemBytes = kOffBar + 256 + 1024;
static_assert(kOffRed + 2 * kMaxSamples * 512 <= kOffX && kOffEpi % 16 == 0 && kOffDnn % 16 == 0 && kOffBar % 8 == 0, "layout");

constexpr int kBarFull = 0, kBarEmpty = 4, kBarImg = 8, kBarX = 12, kNumBars = 15, kBarPrep = 15;

constexpr uint32_t kSpinLimit = 1u << 24;

struct Scratch {
  uint16_t img[kImgBytes / 2];
  float dnn[kB * kSlots];
  unsigned int cnt[4];
};
__device__ __align__(1024) Scratch g_scratch;

#define PROF(slot) do {} while (0)
#define PROFG(slot) do {} while (0)
#define PROFU(slot) do {} while (0)
#define PROF_BEGIN() do {} while (0)
#define PROF_END() do {} while (0)

__host__ __device__ constexpr int xrow(int q, int u, int e) {
  int p = (q == 0) ? u : (q == 1) ? 12 - u : (q == 2) ? (2 * u + 7) % 13 : (2 * (12 - u) + 7) % 13;
  int s = ((q & 1) && (u == 0 || u == 1 || u == 4)) ? 1 : 0;
  return 2 * p + (e ^ s);
}
__host__ __device__ constexpr int feat(int q, int s) { return s < 6 ? 6 * q + s : 24 + (q >> 1); }
__host__ __device__ constexpr int lq(int i) {
  constexpr int L[13] = {0, 1, 4, 6, 2, 3, 5, 7, 8, 9, 10, 11, 12};
  return L[i];
}
__host__ __device__ constexpr int regU(int t) {
  constexpr int U[21] = {0, 0, 0, 0, 0, 1, 1, 1, 1, 2, 2, 2, 3, 3, 3, 4, 4, 5, 0, 1, 4};
  return t < 36 ? U[t >> 1] : U[t - 18];
}
__host__ __device__ constexpr int regV(int t) {
  constexpr int V[21] = {1, 3, 4, 9, 10, 2, 4, 5, 10, 3, 5, 6, 4, 6, 7, 5, 7, 6, 12, 11, 8};
  return t < 36 ? V[t >> 1] : V[t - 18];
}
__host__ __device__ constexpr int xpos(int j) {
  constexpr int P[27] = {8, 18, 16, 6, 19, 4, 1, 5, 14, 23, 17, 3, 10, 0, 20, 13, 24, 2, 12, 11, 21, 25, 15, 26, 22, 7, 9};
  return P[j];
}
__host__ __device__ constexpr int spec(int i) {
  constexpr int S[80] = {13, 13, 23, 22, 23, 23, 8,  8,  4,  4,  20, 20, 21, 21, 9,  8,  18, 18, 18, 19,
                         22, 22, 26, 26, 15, 15, 12, 13, 16, 17, 19, 19, 7,  6,  0,  0,  1,  0,  5,  5,
                         1,  1,  21, 20, 5,  4,  9,  9,  6,  6,  14, 15, 17, 17, 24, 24, 16, 16, 24, 25,
                         11, 11, 25, 25, 3,  2,  3,  3,  12, 12, 2,  2,  14, 14, 7,  7,  10, 10, 11, 10};
  return S[i];
}
struct Tables {
  uint32_t ldsm[32][4];
  uint16_t sent[384];
  uint32_t rowoff[16];
  uint32_t jrow[13][2];
};
constexpr Tables make_tables() {
  Tables t = {};
  for (int lane = 0; lane < 32; lane++) {
    int m = lane >> 3, q = (lane & 7) >> 1, e = lane & 1;
    for (int i = 0; i < 12; i++) {
      int r = i < 7 ? xrow(q, lq(i < 6 ? 2 * i + (m >> 1) : 12), e) : spec((i - 7) * 16 + q * 4 + e * 2 + (m >> 1));
      t.ldsm[lane][i >> 2] |= (uint32_t)(xpos(r) * 9 + (m & 1)) << (8 * (i & 3));
    }
    if (lane < 16) t.rowoff[lane] = (uint32_t)(xpos(lane) * kXPitch) | (uint32_t)(xpos(lane < 10 ? lane + 16 : lane) * kXPitch) << 16;
  }
  for (int i = 0; i < 384; i++) {
    int slot = 2 * (i >> 4) + ((i >> 3) & 1) - 4, q = (i & 7) >> 1, e = i & 1, a = 0, b = 0;
    if (slot < 0) {
      const bool dup = slot == -1 && q > 0;
      a = dup ? 27 : xrow(q, lq(slot + 4), e);
      b = dup ? 27 : 26;
    } else if (slot < 39) {
      a = xrow(q, regU(slot), slot < 36 ? (slot & 1) : e);
      b = xrow(q, regV(slot), e);
    } else {
      a = spec((slot - 39) * 16 + q * 4 + e * 2);
      b = spec((slot - 39) * 16 + q * 4 + e * 2 + 1);
    }
    t.sent[i] = (uint16_t)(a <= b ? a | b << 8 : b | a << 8);
  }
  for (int u = 0; u < 13; u++)
    for (int k = 0; k < 8; k++) t.jrow[u][k >> 2] |= (uint32_t)xrow(k >> 1, u, k & 1) << (8 * (k & 3));
  return t;
}
__device__ const __align__(16) Tables g_tab = make_tables();

template <int I, int N, class Fn>
__device__ __forceinline__ void static_for(Fn&& f) {
  if constexpr (I < N) {
    f(std::integral_constant<int, I>{});
    static_for<I + 1, N>(f);
  }
}

__device__ __forceinline__ void mbar_init(uint32_t bar, uint32_t count) {
  asm volatile("mbarrier.init.shared::cta.b64 [%0], %1;" ::"r"(bar), "r"(count) : "memory");
}
__device__ __forceinline__ void mbar_expect_tx(uint32_t bar, uint32_t bytes) {
  asm volatile("mbarrier.arrive.expect_tx.shared::cta.b64 _, [%0], %1;" ::"r"(bar), "r"(bytes) : "memory");
}
__device__ __forceinline__ void mbar_arrive_cluster(uint32_t bar, uint32_t cta) {
  asm volatile(
      "{\n.reg .b32 ra;\nmapa.shared::cluster.u32 ra, %0, %1;\n"
      "mbarrier.arrive.shared::cluster.b64 _, [ra];\n}" ::"r"(bar), "r"(cta) : "memory");
}
__device__ __forceinline__ uint32_t mbar_try(uint32_t bar, uint32_t parity) {
  uint32_t ok;
  asm volatile(
      "{\n.reg .pred p;\nmbarrier.try_wait.parity.shared::cta.b64 p, [%1], %2;\nselp.u32 %0, 1, 0, p;\n}"
      : "=r"(ok) : "r"(bar), "r"(parity) : "memory");
  return ok;
}
__device__ __forceinline__ void mbar_wait(uint32_t bar, uint32_t parity) {
  uint32_t n = 0;
  while (!mbar_try(bar, parity)) {
    if (++n > kSpinLimit) __trap();
  }
}
__device__ __forceinline__ void wait_counter(const unsigned int* p, unsigned int target) {
  uint32_t n = 0, v;
  while (true) {
    asm volatile("ld.acquire.gpu.global.u32 %0, [%1];" : "=r"(v) : "l"(p) : "memory");
    if (v >= target) break;
    if (++n > (1u << 22)) __trap();
    __nanosleep(20);
  }
}
__device__ __forceinline__ void red_release(unsigned int* p) {
  asm volatile("red.release.gpu.global.add.u32 [%0], 1;" ::"l"(p) : "memory");
}
__device__ __forceinline__ void bulk_load(uint32_t dst, const void* src, uint32_t bytes, uint32_t bar) {
  asm volatile("cp.async.bulk.shared::cluster.global.mbarrier::complete_tx::bytes [%0], [%1], %2, [%3];"
               ::"r"(dst), "l"(src), "r"(bytes), "r"(bar) : "memory");
}
__device__ __forceinline__ void tma_load_mc(uint32_t dst, const CUtensorMap* map, int c0, int c1, uint32_t bar) {
  asm volatile(
      "cp.async.bulk.tensor.2d.shared::cluster.global.mbarrier::complete_tx::bytes.multicast::cluster"
      " [%0], [%1, {%3, %4}], [%2], %5;"
      ::"r"(dst), "l"(map), "r"(bar), "r"(c0), "r"(c1), "h"((uint16_t)3) : "memory");
}
__device__ __forceinline__ void cp_async16(uint32_t dst, const void* src) {
  asm volatile("cp.async.cg.shared.global [%0], [%1], 16;" ::"r"(dst), "l"(src) : "memory");
}
__device__ __forceinline__ void cp_async16_if(bool on, uint32_t dst, const void* src) {
  asm volatile("{.reg .pred p; setp.ne.u32 p, %2, 0; @p cp.async.cg.shared.global [%0], [%1], 16;}"
               ::"r"(dst), "l"(src), "r"((uint32_t)on) : "memory");
}
__device__ __forceinline__ void cp_async_arrive(uint32_t bar) {
  asm volatile("cp.async.mbarrier.arrive.noinc.shared::cta.b64 [%0];" ::"r"(bar) : "memory");
}
__device__ __forceinline__ void fence_async_smem() { asm volatile("fence.proxy.async.shared::cta;" ::: "memory"); }
__device__ __forceinline__ void fence_async_global() { asm volatile("fence.proxy.async.global;" ::: "memory"); }
__device__ __forceinline__ void cp_async4(uint32_t dst, const void* src) {
  asm volatile("cp.async.ca.shared.global [%0], [%1], 4;" ::"r"(dst), "l"(src) : "memory");
}
__device__ __forceinline__ uint32_t ld_early16(const void* p) {
  uint32_t v;
  asm volatile("ld.global.nc.u16 %0, [%1];" : "=r"(v) : "l"(p));
  return v;
}
__device__ __forceinline__ uint32_t ld_early32(const void* p) {
  uint32_t v;
  asm volatile("ld.global.nc.u32 %0, [%1];" : "=r"(v) : "l"(p));
  return v;
}
__device__ __forceinline__ uint2 ld_early64(const void* p) {
  uint2 v;
  asm volatile("ld.global.nc.v2.u32 {%0,%1}, [%2];" : "=r"(v.x), "=r"(v.y) : "l"(p));
  return v;
}
__device__ __forceinline__ uint4 ld_early128(const void* p) {
  uint4 v;
  asm volatile("ld.global.nc.v4.u32 {%0,%1,%2,%3}, [%4];" : "=r"(v.x), "=r"(v.y), "=r"(v.z), "=r"(v.w) : "l"(p));
  return v;
}
__device__ __forceinline__ void cp_async_wait_all() { asm volatile("cp.async.wait_all;" ::: "memory"); }
__device__ __forceinline__ const uint8_t* row_ptr(const uint8_t* base, uint32_t row) {
  uint64_t p;
  asm("mad.wide.u32 %0, %1, 256, %2;" : "=l"(p) : "r"(row), "l"(base));
  return reinterpret_cast<const uint8_t*>(p);
}
template <int ID, int N>
__device__ __forceinline__ void bar_sync() { asm volatile("bar.sync %0, %1;" ::"n"(ID), "n"(N) : "memory"); }
template <int ID, int N>
__device__ __forceinline__ void bar_arrive() { asm volatile("bar.arrive %0, %1;" ::"n"(ID), "n"(N) : "memory"); }
__device__ __forceinline__ void wg_fence() { asm volatile("wgmma.fence.sync.aligned;" ::: "memory"); }
__device__ __forceinline__ void wg_commit() { asm volatile("wgmma.commit_group.sync.aligned;" ::: "memory"); }
template <int N>
__device__ __forceinline__ void wg_wait() { asm volatile("wgmma.wait_group.sync.aligned %0;" ::"n"(N) : "memory"); }
template <int N>
__device__ __forceinline__ void pin(float (&d)[N]) {
#pragma unroll
  for (int i = 0; i < N; i++) asm volatile("" : "+f"(d[i])::"memory");
}
__device__ __forceinline__ void ldsm4(uint32_t& r0, uint32_t& r1, uint32_t& r2, uint32_t& r3, uint32_t addr) {
  asm volatile("ldmatrix.sync.aligned.m8n8.x4.trans.shared.b16 {%0,%1,%2,%3}, [%4];"
               : "=r"(r0), "=r"(r1), "=r"(r2), "=r"(r3) : "r"(addr) : "memory");
}
__device__ __forceinline__ void ldsm2(uint32_t& r0, uint32_t& r1, uint32_t addr) {
  asm volatile("ldmatrix.sync.aligned.m8n8.x2.trans.shared.b16 {%0,%1}, [%2];" : "=r"(r0), "=r"(r1) : "r"(addr) : "memory");
}
__device__ __forceinline__ uint32_t mul2(uint32_t a, uint32_t b) {
  uint32_t r;
  asm("mul.rn.bf16x2 %0, %1, %2;" : "=r"(r) : "r"(a), "r"(b));
  return r;
}
template <int HI>
__device__ __forceinline__ uint32_t mul_dup(uint32_t a, uint32_t b) {
  uint32_t r;
  if constexpr (HI)
    asm("{.reg .b16 l,h; .reg .b32 t; mov.b32 {l,h}, %1; mov.b32 t, {h,h}; mul.rn.bf16x2 %0, t, %2;}" : "=r"(r) : "r"(a), "r"(b));
  else
    asm("{.reg .b16 l,h; .reg .b32 t; mov.b32 {l,h}, %1; mov.b32 t, {l,l}; mul.rn.bf16x2 %0, t, %2;}" : "=r"(r) : "r"(a), "r"(b));
  return r;
}
__device__ __forceinline__ uint32_t pack2(float lo, float hi) {
  uint32_t r;
  asm("cvt.rn.bf16x2.f32 %0, %1, %2;" : "=r"(r) : "f"(hi), "f"(lo));
  return r;
}
__device__ __forceinline__ float bf2f(uint16_t v) { return __uint_as_float((uint32_t)v << 16); }
__device__ __forceinline__ uint16_t f2bf(float v) { return __bfloat16_as_ushort(__float2bfloat16_rn(v)); }

template <int ACC>
__device__ __forceinline__ void wgmma_rs32(float (&d)[16], const uint32_t (&a)[4], uint64_t desc) {
  asm volatile(
      "wgmma.mma_async.sync.aligned.m64n32k16.f32.bf16.bf16 "
      "{%0,%1,%2,%3,%4,%5,%6,%7,%8,%9,%10,%11,%12,%13,%14,%15}, {%16,%17,%18,%19}, %20, %21, 1, 1, 0;"
      : "+f"(d[0]), "+f"(d[1]), "+f"(d[2]), "+f"(d[3]), "+f"(d[4]), "+f"(d[5]), "+f"(d[6]), "+f"(d[7]), "+f"(d[8]),
        "+f"(d[9]), "+f"(d[10]), "+f"(d[11]), "+f"(d[12]), "+f"(d[13]), "+f"(d[14]), "+f"(d[15])
      : "r"(a[0]), "r"(a[1]), "r"(a[2]), "r"(a[3]), "l"(desc), "n"(ACC));
}
template <int ACC>
__device__ __forceinline__ void wgmma_rs56(float (&d)[28], const uint32_t (&a)[4], uint64_t desc) {
  asm volatile(
      "wgmma.mma_async.sync.aligned.m64n56k16.f32.bf16.bf16 "
      "{%0,%1,%2,%3,%4,%5,%6,%7,%8,%9,%10,%11,%12,%13,%14,%15,%16,%17,%18,%19,%20,%21,%22,%23,%24,%25,%26,%27}, "
      "{%28,%29,%30,%31}, %32, %33, 1, 1, 0;"
      : "+f"(d[0]), "+f"(d[1]), "+f"(d[2]), "+f"(d[3]), "+f"(d[4]), "+f"(d[5]), "+f"(d[6]), "+f"(d[7]), "+f"(d[8]),
        "+f"(d[9]), "+f"(d[10]), "+f"(d[11]), "+f"(d[12]), "+f"(d[13]), "+f"(d[14]), "+f"(d[15]), "+f"(d[16]),
        "+f"(d[17]), "+f"(d[18]), "+f"(d[19]), "+f"(d[20]), "+f"(d[21]), "+f"(d[22]), "+f"(d[23]), "+f"(d[24]),
        "+f"(d[25]), "+f"(d[26]), "+f"(d[27])
      : "r"(a[0]), "r"(a[1]), "r"(a[2]), "r"(a[3]), "l"(desc), "n"(ACC));
}
#define XD_ACC8(o) "+f"(d[o]), "+f"(d[o + 1]), "+f"(d[o + 2]), "+f"(d[o + 3]), "+f"(d[o + 4]), "+f"(d[o + 5]), "+f"(d[o + 6]), "+f"(d[o + 7])
__device__ __forceinline__ void wgmma_ss256(float (&d)[128], uint64_t da, uint64_t db) {
  asm volatile(
      "wgmma.mma_async.sync.aligned.m64n256k16.f32.bf16.bf16 "
      "{%0,%1,%2,%3,%4,%5,%6,%7,%8,%9,%10,%11,%12,%13,%14,%15,%16,%17,%18,%19,%20,%21,%22,%23,%24,%25,%26,%27,%28,%29,%30,%31,"
      "%32,%33,%34,%35,%36,%37,%38,%39,%40,%41,%42,%43,%44,%45,%46,%47,%48,%49,%50,%51,%52,%53,%54,%55,%56,%57,%58,%59,%60,%61,%62,%63,"
      "%64,%65,%66,%67,%68,%69,%70,%71,%72,%73,%74,%75,%76,%77,%78,%79,%80,%81,%82,%83,%84,%85,%86,%87,%88,%89,%90,%91,%92,%93,%94,%95,"
      "%96,%97,%98,%99,%100,%101,%102,%103,%104,%105,%106,%107,%108,%109,%110,%111,%112,%113,%114,%115,%116,%117,%118,%119,%120,%121,%122,%123,%124,%125,%126,%127}, "
      "%128, %129, 1, 1, 1, 0, 1;"
      : XD_ACC8(0), XD_ACC8(8), XD_ACC8(16), XD_ACC8(24), XD_ACC8(32), XD_ACC8(40), XD_ACC8(48), XD_ACC8(56),
        XD_ACC8(64), XD_ACC8(72), XD_ACC8(80), XD_ACC8(88), XD_ACC8(96), XD_ACC8(104), XD_ACC8(112), XD_ACC8(120)
      : "l"(da), "l"(db));
}
__device__ __forceinline__ uint64_t make_desc(uint32_t addr, uint32_t lbo, uint32_t sbo, uint64_t swz) {
  return (uint64_t)((addr & 0x3FFFF) >> 4) | ((uint64_t)(lbo >> 4) << 16) | ((uint64_t)(sbo >> 4) << 32) | (swz << 62);
}

constexpr int kLayer = 26 * 26 * 26;
constexpr int kPrepW5 = 0, kPrepRow = 35200, kPrepCol = kPrepRow + 3 * 1376, kPrepW = kPrepCol + 4 * 2080;
constexpr int kPrepV = kPrepW + 320, kPrepP = kPrepV + 26 * 28 * 4;

__device__ __forceinline__ void stage_weights(int c, uint32_t sbase, const uint16_t* __restrict__ W,
                                              const uint16_t* __restrict__ wout) {
  const int tid = threadIdx.x, cf = feat(c / 7, c % 7);
  const uint8_t* Wb = reinterpret_cast<const uint8_t*>(W);
  {
#pragma unroll
    for (int r = 0; r < 2; r++) {
      const int i = tid + r * kThreads, sl = i / 130, ch = i - 130 * sl, h = ch / 5;
      const int lay = sl == 0 ? 4 : sl == 1 ? 3 : sl - 1;
      if (i < 520) cp_async16(sbase + kPrepCol + i * 16, Wb + lay * kLayer * 2 + ((h * 1352 + cf * 52) & ~15) + (ch - 5 * h) * 16);
    }
  }
  if (tid < 258) {
    const int sl = tid / 86, lay = sl == 0 ? 1 : sl == 1 ? 2 : 0;
    cp_async16(sbase + kPrepRow + tid * 16, Wb + lay * kLayer * 2 + ((cf * 1352) & ~15) + (tid - 86 * sl) * 16);
  } else if (tid >= 288 && tid < 288 + 39) {
    asm volatile("cp.async.ca.shared.global [%0], [%1], 8;" ::"r"(sbase + kPrepW + (tid - 288) * 8), "l"(wout + 4 * (tid - 288)) : "memory");
  }
}
__device__ __forceinline__ const uint16_t* rowslab(const uint8_t* smem, int sl, int cf) {
  return reinterpret_cast<const uint16_t*>(smem + kPrepRow + sl * 1376 + (cf & 1) * 8);
}
__device__ __forceinline__ const uint16_t* colslab(const uint8_t* smem, int sl, int cf, int h) {
  return reinterpret_cast<const uint16_t*>(smem + kPrepCol + sl * 2080 + h * 80 + ((h * 8 + cf * 52) & 15));
}

__device__ __forceinline__ void copy_item(int item, int cq, int cs, const uint8_t* smem, uint8_t* imgb, uint2 jr) {
  const int lay = item / 86, slot = item - 86 * lay, s = slot < 78 ? slot / 13 : 6, cf = feat(cq, cs);
  uint32_t v[8];
#pragma unroll
  for (int q = 0; q < 4; q++) {
    const int fi = feat(q, s);
    const uint16_t* src = lay == 1 ? colslab(smem, 1, cf, fi) : rowslab(smem, lay >> 1, cf) + fi * 26;
#pragma unroll
    for (int e = 0; e < 2; e++) {
      v[2 * q + e] = src[((q < 2 ? jr.x : jr.y) >> (8 * (2 * (q & 1) + e))) & 255];
      if (slot == 85 || (slot == 84 && (q & 1))) v[2 * q + e] = 0;
    }
  }
  uint4 o = make_uint4(v[0] | (v[1] << 16), v[2] | (v[3] << 16), v[4] | (v[5] << 16), v[6] | (v[7] << 16));
  if (lay != 0 && cs == 6 && (cq & 1)) o = make_uint4(0, 0, 0, 0);
  *reinterpret_cast<uint4*>(imgb + kImgF2 + lay * kImgLBytes + (slot >> 1) * 1024 + (cs >> 1) * 256 + (slot & 1) * 128 +
                            (2 * cq + (cs & 1)) * 16) = o;
}
__device__ __forceinline__ uint2 item_rows(const Tables* tab, int item) {
  const int slot = item % 86;
  return ld_early64(tab->jrow[slot >= 78 ? min(slot - 78, 6) : slot % 13]);
}

__device__ __forceinline__ void build_image(int c, uint8_t* smem, uint16_t* __restrict__ img, uint32_t ab) {
  const uint16_t* sw = reinterpret_cast<const uint16_t*>(smem + kPrepW);
  float* sV = reinterpret_cast<float*>(smem + kPrepV);
  float* sP = reinterpret_cast<float*>(smem + kPrepP);
  const int tid = threadIdx.x, half = (tid >> 4) & 1, u16 = (tid >> 5) * 16 + (tid & 15);
  const int cq = c / 7, cs = c - 7 * cq, cf = feat(cq, cs);
  {
    const uint2* p = reinterpret_cast<const uint2*>(smem + kPrepW5) + min(u16, 168) + half * 13 * 169;
    const uint16_t* w5 = sw + 5 * 26 + half * 13;
    float v0 = 0.f, v1 = 0.f, v2 = 0.f, v3 = 0.f;
#pragma unroll
    for (int g = 0; g < 13; g++) {
      const uint2 w = p[g * 169];
      const float s = bf2f(w5[g]);
      v0 = fmaf(s, __uint_as_float(w.x << 16), v0);
      v1 = fmaf(s, __uint_as_float(w.x & 0xffff0000u), v1);
      v2 = fmaf(s, __uint_as_float(w.y << 16), v2);
      v3 = fmaf(s, __uint_as_float(w.y & 0xffff0000u), v3);
    }
    const float o0 = __shfl_xor_sync(0xffffffffu, half ? v0 : v2, 16), o1 = __shfl_xor_sync(0xffffffffu, half ? v1 : v3, 16);
    const int w = 2 * u16 + half;
    if (u16 < 169) *reinterpret_cast<float2*>(sV + 2 * w + 2 * (w / 13)) = make_float2((half ? v2 : v0) + o0, (half ? v3 : v1) + o1);
    if (tid < 26) *reinterpret_cast<float2*>(sV + tid * 28 + 26) = make_float2(bf2f(sw[4 * 26 + tid]), 0.f);
  }
  PROF(43 + (tid >> 7));
  __syncthreads();
  {
    const int un = min(u16, 181), pa = un / 14, pb = un - 14 * pa;
    const float2* vp = reinterpret_cast<const float2*>(sV) + pb + half * 13 * 14;
    float r0 = 0.f, r1 = 0.f, r2 = 0.f, r3 = 0.f;
#pragma unroll
    for (int h = 0; h < 13; h++) {
      const uint32_t w = reinterpret_cast<const uint32_t*>(colslab(smem, 0, cf, half * 13 + h))[pa];
      const float2 v = vp[h * 14];
      const float wl = __uint_as_float(w << 16), wh = __uint_as_float(w & 0xffff0000u);
      r0 = fmaf(wl, v.x, r0);
      r1 = fmaf(wl, v.y, r1);
      r2 = fmaf(wh, v.x, r2);
      r3 = fmaf(wh, v.y, r3);
    }
    const float o0 = __shfl_xor_sync(0xffffffffu, half ? r0 : r2, 16), o1 = __shfl_xor_sync(0xffffffffu, half ? r1 : r3, 16);
    if (u16 < 182) reinterpret_cast<float2*>(sP)[pa * 28 + half * 14 + pb] = make_float2((half ? r2 : r0) + o0, (half ? r3 : r1) + o1);
  }
  PROF(49 + (tid >> 7));
  __syncthreads();
  const int a = ab & 255, b = ab >> 8;
  const uint16_t* sX = rowslab(smem, 2, cf);
  float x1w = 0.f, g4w = 0.f;
  if (b < 26) x1w = a == b ? bf2f(sX[a * 27]) : bf2f(sX[a * 26 + b]) + bf2f(sX[b * 26 + a]);
  if (a == 26) g4w = bf2f(sw[3 * 26 + cf]);
  else if (a < 26) g4w = (b < 26 && a != b) ? sP[a * 28 + b] + sP[b * 28 + a] : sP[a * 28 + b];
  const int s4 = cs + 7, base = (tid >> 4) * 896 + ((tid >> 3) & 1) * 64 + (tid & 7);
  img[base + (cs >> 1) * 128 + (2 * cq + (cs & 1)) * 8] = f2bf(x1w);
  img[base + (s4 >> 1) * 128 + (2 * cq + (s4 & 1)) * 8] = f2bf(g4w);
  PROF(52 + (tid >> 7));
}

__device__ __forceinline__ void build_full_stages(int c, uint8_t* smem, uint16_t* __restrict__ img, uint2 jr) {
  const uint16_t* sw = reinterpret_cast<const uint16_t*>(smem + kPrepW);
  uint8_t* imgb = reinterpret_cast<uint8_t*>(img);
  const int tid = threadIdx.x;
  const int cq = c / 7, cs = c - 7 * cq, cf = feat(cq, cs);
  if (tid < 258) {
    copy_item(tid, cq, cs, smem, imgb, jr);
  } else if (tid < 258 + 30) {
    for (int i = c * 30 + tid - 258; i < 9 * 86 + 85; i += kPrepCtas * 30) {
      const int col = i / 86, slot = i - 86 * col, lay = col < 9 ? col / 3 : 1, q = col < 9 ? col - 3 * lay + 1 : 0;
      *reinterpret_cast<uint4*>(imgb + kImgF2 + lay * kImgLBytes + (slot >> 1) * 1024 + 3 * 256 + (slot & 1) * 128 +
                                (2 * q + 1) * 16) = make_uint4(0, 0, 0, 0);
    }
    const int lay = (tid - 258) >> 3, k = (tid - 258) & 7;
    if (c == 1 && lay < 3) img[(kImgF2 + lay * kImgLBytes) / 2 + 42 * 512 + 3 * 128 + 64 + 8 + k] = sw[6 * (k >> 1) + 2 * lay + (k & 1)];
  } else if (tid >= 320 && (tid & 31) < 26) {
    const int l = tid < 352 ? 1 : 2, u = (tid & 31) >> 1, e = tid & 1;
    if (cs < 6 || u < 7) {
      const int slot = cs < 6 ? cs * 13 + u : 78 + u;
      float v = 0.f;
      if (slot < 84 || !(cq & 1)) {
        const int j = ((cq < 2 ? jr.x : jr.y) >> (8 * (2 * (cq & 1) + e))) & 255;
#pragma unroll
        for (int h = 0; h < 26; h++) v = fmaf(bf2f(sw[26 * l + h]), bf2f(colslab(smem, 1 + l, cf, h)[j]), v);
      }
      img[(kImgF2 + (l - 1) * 2 * kImgLBytes) / 2 + (slot >> 1) * 512 + 3 * 128 + (slot & 1) * 64 + 8 + 2 * cq + e] = f2bf(v);
    }
  }
}

#define XD_GROUP 2
constexpr int kGroup = XD_GROUP;

template <int T>
__device__ __forceinline__ void slot_full(uint32_t& r0, uint32_t& r1, const uint32_t (&x)[2][13], const uint32_t (&y)[7],
                                          const uint32_t (&pad)[2]) {
  if constexpr (T >= 85) {
    r0 = pad[0];
    r1 = pad[1];
  } else {
    constexpr int s = T < 78 ? T / 13 : 6, u = T < 78 ? T % 13 : T - 78;
    r0 = mul_dup<0>(y[s], x[0][u]);
    r1 = mul_dup<1>(y[s], x[1][u]);
  }
}

template <class Late>
__device__ __forceinline__ void full_stage(float (&acc)[16], const uint32_t (&x)[2][13], const uint32_t (&y)[7],
                                           const uint32_t (&pad)[2], uint64_t desc, Late&& late) {
  static_for<0, (kStepsL + kGroup - 1) / kGroup>([&](auto gi) {
    constexpr int t0 = decltype(gi)::value * kGroup;
    constexpr int n = (kStepsL - t0) < kGroup ? (kStepsL - t0) : kGroup;
    uint32_t a[n][4];
    static_for<0, n>([&](auto j) {
      constexpr int t = t0 + decltype(j)::value;
      slot_full<2 * t>(a[decltype(j)::value][0], a[decltype(j)::value][1], x, y, pad);
      slot_full<2 * t + 1>(a[decltype(j)::value][2], a[decltype(j)::value][3], x, y, pad);
    });
    wg_fence();
    static_for<0, n>([&](auto j) {
      constexpr int t = t0 + decltype(j)::value;
      wgmma_rs32<(t > 0)>(acc, a[decltype(j)::value], desc + (uint64_t)(t * 64));
    });
    wg_commit();
    wg_wait<1>();
    if constexpr (t0 == 16 * kGroup) late();
  });
}
template <int OFF, int N>
__device__ __forceinline__ void pack_slots(uint32_t (&y)[7], const float (&acc)[N]) {
#pragma unroll
  for (int s = 0; s < 7; s++) y[s] = pack2(acc[4 * ((s + OFF) >> 1) + ((s + OFF) & 1)], acc[4 * ((s + OFF) >> 1) + 2 + ((s + OFF) & 1)]);
}

__device__ __forceinline__ void tile_begin(uint32_t (&x)[2][13], float (&accS)[28], const uint32_t (&xa)[12], uint32_t xo,
                                           uint64_t dS) {
  static_for<0, 6>([&](auto ii) {
    constexpr int i = decltype(ii)::value;
    ldsm4(x[0][lq(2 * i)], x[1][lq(2 * i)], x[0][lq(2 * i + 1)], x[1][lq(2 * i + 1)], xa[i] + xo);
  });
  ldsm2(x[0][12], x[1][12], xa[6] + xo);
  const uint32_t l0[4] = {x[0][lq(0)], x[1][lq(0)], x[0][lq(1)], x[1][lq(1)]};
  const uint32_t l1[4] = {x[0][lq(2)], x[1][lq(2)], x[0][lq(3)], x[1][lq(3)]};
  wg_fence();
  wgmma_rs56<0>(accS, l0, dS);
  wgmma_rs56<1>(accS, l1, dS + 112);
  wg_commit();
  wg_wait<1>();
}

template <class Hook, class Hook2>
__device__ __forceinline__ void stage_s_rest(const uint32_t (&x)[2][13], float (&accS)[28], const uint32_t (&xa)[12], uint32_t xo,
                                             uint64_t dS, Hook&& hook, Hook2&& hook2) {
  uint32_t e[5][4];
  static_for<1, kStepsS / 2>([&](auto gi) {
    constexpr int t0 = decltype(gi)::value * 2;
    if constexpr (t0 == 18) ldsm4(e[0][0], e[0][1], e[0][2], e[0][3], xa[7] + xo);
    if constexpr (t0 == 20) {
#pragma unroll
      for (int i = 1; i < 5; i++) ldsm4(e[i][0], e[i][1], e[i][2], e[i][3], xa[7 + i] + xo);
    }
    uint32_t a[2][4];
    static_for<0, 4>([&](auto j) {
      constexpr int jj = decltype(j)::value, slot = 2 * t0 + jj - 4;
      uint32_t& r0 = a[jj >> 1][(jj & 1) * 2];
      uint32_t& r1 = a[jj >> 1][(jj & 1) * 2 + 1];
      if constexpr (slot < 36) {
        r0 = mul_dup<slot & 1>(x[0][regU(slot)], x[0][regV(slot)]);
        r1 = mul_dup<slot & 1>(x[1][regU(slot)], x[1][regV(slot)]);
      } else if constexpr (slot < 39) {
        r0 = mul2(x[0][regU(slot)], x[0][regV(slot)]);
        r1 = mul2(x[1][regU(slot)], x[1][regV(slot)]);
      } else {
        r0 = mul2(e[slot - 39][0], e[slot - 39][2]);
        r1 = mul2(e[slot - 39][1], e[slot - 39][3]);
      }
    });
    wg_fence();
    wgmma_rs56<1>(accS, a[0], dS + (uint64_t)(t0 * 112));
    wgmma_rs56<1>(accS, a[1], dS + (uint64_t)((t0 + 1) * 112));
    wg_commit();
    wg_wait<1>();
    if constexpr (t0 == 2) hook();
    if constexpr (t0 == 8) hook2();
  });
  wg_wait<0>();
  pin(accS);
}

template <class WaitX, class Prefetch, class Last, class Emit>
__device__ __forceinline__ void cin_loop(int n, const uint32_t (&xa)[12], uint32_t xbase, float w06, uint32_t sbase,
                                         uint32_t imgbar, WaitX&& waitx, Prefetch&& prefetch, Last&& last, Emit&& emit) {
  uint64_t dS = make_desc(sbase, 128, 256, 0);
  uint32_t x[2][13];
  float accS[28];
  waitx(0);
  mbar_wait(imgbar, 0);
  tile_begin(x, accS, xa, xbase, dS);
  stage_s_rest(x, accS, xa, xbase, dS, [] {}, [&] { prefetch(0); });
  mbar_wait(imgbar + 8, 0);
#pragma unroll 1
  for (int it = 0;; it++) {
    const bool first = it == 0, more = it + 1 < n;
    dS += (uint32_t)it >> 30;
    uint32_t y1[7], y4[7];
    pack_slots<0>(y1, accS);
    pack_slots<7>(y4, accS);
    uint32_t pad[3][2];
#pragma unroll
    for (int l = 0; l < 3; l++) {
      pad[l][0] = pack2(accS[4 * l], accS[4 * l + 1]);
      pad[l][1] = pack2(accS[4 * l + 2], accS[4 * l + 3]);
    }
    float sum0 = accS[12], sum1 = accS[14];
    float accA[16], accG[16], accX[16];
    full_stage(accA, x, y1, pad[0], dS + (uint64_t)(kImgF2 >> 4), [&] { if (first) mbar_wait(imgbar + 16, 0); });
    full_stage(accG, x, y4, pad[1], dS + (uint64_t)(kImgB3 >> 4), [&] {
      if (first) mbar_wait(imgbar + 24, 0);
      if (!more) last();
    });
    pin(accA);
    uint32_t y2[7];
    pack_slots<0>(y2, accA);
    sum0 = fmaf(w06, sum0, accA[13]);
    sum1 = fmaf(w06, sum1, accA[15]);
    full_stage(accX, x, y2, pad[2], dS + (uint64_t)(kImgF3 >> 4), [&] { if (more) waitx(it + 1); });
    auto finish = [&] {
      pin(accG);
      pin(accX);
#pragma unroll
      for (int s = 0; s < 7; s++) {
        sum0 = fmaf(accG[4 * (s >> 1) + (s & 1)], accX[4 * (s >> 1) + (s & 1)], sum0);
        sum1 = fmaf(accG[4 * (s >> 1) + 2 + (s & 1)], accX[4 * (s >> 1) + 2 + (s & 1)], sum1);
      }
      emit(it, (sum0 + sum1) + ((accG[13] + accX[13]) + (accG[15] + accX[15])));
    };
    if (!more) {
      wg_wait<0>();
      finish();
      break;
    }
    const uint32_t xo = xbase + ((it + 1) & 1) * kXBufBytes;
    tile_begin(x, accS, xa, xo, dS);
    stage_s_rest(x, accS, xa, xo, dS, finish, [&] { prefetch(it + 1); });
  }
}

struct XLoader {
  const uint8_t* src;
  uint32_t i0, i1, d0, d1;
  __device__ __forceinline__ void init(const uint8_t* table, uint32_t rowoff) {
    const uint32_t t = threadIdx.x & 127;
    src = table + (t & 7) * 16;
    i0 = (t >> 3) * 4;
    i1 = i0 + (t < 8 * (kF - 16) ? 64 : 0);
    d0 = (rowoff & 0xffffu) + (t & 7) * 16;
    d1 = (rowoff >> 16) + (t & 7) * 16;
  }
  __device__ __forceinline__ void operator()(uint32_t sbase, int tile, int wg, int par) const {
    const uint32_t ia = sbase + kOffIdx + tile * 128, buf = sbase + kOffX + (2 * wg + par) * kXBufBytes;
    uint32_t r0, r1;
    asm volatile("ld.shared.u32 %0, [%1];" : "=r"(r0) : "r"(ia + i0) : "memory");
    asm volatile("ld.shared.u32 %0, [%1];" : "=r"(r1) : "r"(ia + i1) : "memory");
    uint64_t p0, p1;
    asm("mad.wide.u32 %0, %1, 128, %2;" : "=l"(p0) : "r"(r0), "l"(src));
    asm("mad.wide.u32 %0, %1, 128, %2;" : "=l"(p1) : "r"(r1), "l"(src));
    cp_async16(buf + d0, reinterpret_cast<const void*>(p0));
    cp_async16(buf + d1, reinterpret_cast<const void*>(p1));
    cp_async_arrive(sbase + kOffBar + 8 * (kBarX + wg));
  }
};
template <int NTH>
__device__ __forceinline__ void load_half_rows(uint32_t (&v)[3], const int* __restrict__ idx, int tile0, int ntile, int t) {
#pragma unroll
  for (int r = 0; r < 3; r++) {
    const int i = t + r * NTH, tile = tile0 + min(i >> 5, ntile - 1);
    v[r] = ld_early32(idx + (tile >> 1) * kF + min(i & 31, kF - 1));
  }
}
template <int NTH>
__device__ __forceinline__ void store_half_rows(uint32_t* s_idx, const uint32_t (&v)[3], int tile0, int ntile, int t) {
#pragma unroll
  for (int r = 0; r < 3; r++) s_idx[t + r * NTH] = 2 * v[r] + ((tile0 + min((t + r * NTH) >> 5, ntile - 1)) & 1);
}

__device__ __forceinline__ void ones_rows(uint8_t* smem, int t) {
  if (t < 48)
    *reinterpret_cast<uint4*>(smem + kOffX + (t >> 3) * kXBufBytes + xpos(26) * kXPitch + (t & 7) * 16) =
        make_uint4(0x3F803F80u, 0x3F803F80u, 0x3F803F80u, 0x3F803F80u);
}

__device__ __forceinline__ void publish(float* slot, float v) {
  uint32_t bits = __float_as_uint(v);
  if (bits == 0) bits = 0x80000000u;
  asm volatile("st.relaxed.gpu.global.u32 [%0], %1;" ::"l"(slot), "r"(bits) : "memory");
}

__device__ __forceinline__ void await_image(Scratch* scr) {
  wait_counter(&scr->cnt[0], kPrepCtas);
  fence_async_global();
}
__device__ __forceinline__ void ack_image(Scratch* scr) {
  if (atomicAdd(&scr->cnt[1], 1u) == kCtas - 1) {
    scr->cnt[0] = 0;
    scr->cnt[1] = 0;
  }
}
__device__ __forceinline__ void load_image_part(uint32_t sbase, const Scratch* scr, int p) {
  const uint32_t off = p == 0 ? 0 : kImgF2 + (p - 1) * kImgLBytes, bytes = p == 0 ? kImgSBytes : kImgLBytes;
  const uint32_t bar = sbase + kOffBar + 8 * (kBarImg + p);
  mbar_expect_tx(bar, bytes);
  bulk_load(sbase + off, reinterpret_cast<const uint8_t*>(scr->img) + off, bytes, bar);
}

__global__ void __cluster_dims__(2, 1, 1) __launch_bounds__(kThreads, 1)
xdeepfm_kernel(const __grid_constant__ CUtensorMap tmW, const int* __restrict__ idx, const uint8_t* __restrict__ table,
               const uint16_t* __restrict__ wcin, const uint16_t* __restrict__ wout, const uint16_t* __restrict__ b1,
               const uint16_t* __restrict__ w2, const uint16_t* __restrict__ bout, uint16_t* __restrict__ out,
               Scratch* scr, const Tables* __restrict__ tab) {
  extern __shared__ uint8_t smem_raw[];
  const uint32_t raw = (uint32_t)__cvta_generic_to_shared(smem_raw);
  const uint32_t sbase = (raw + 1023u) & ~1023u;
  uint8_t* smem = smem_raw + (sbase - raw);
  const int tid = threadIdx.x, lane = tid & 31;
  const int wg = __shfl_sync(0xffffffffu, tid >> 7, 0);
  const int warp = __shfl_sync(0xffffffffu, (tid >> 5) & 3, 0);
  const int cta = blockIdx.x;
  const bool gemm = cta >= kPrepCtas;
  const uint32_t bars = sbase + kOffBar;
  uint32_t* s_idx = reinterpret_cast<uint32_t*>(smem + kOffIdx);

  const int g = cta - kPrepCtas;
  const int tile0 = gemm ? kPrepTilesTotal + g * kGemmTiles : cta * kPrepBase + min(cta, kPrepRem);
  const int ntile = gemm ? kGemmTiles : kPrepBase + (cta < kPrepRem ? 1 : 0);
  const int toff = tile0 & 1, samp0 = tile0 >> 1, nsamp = (toff + ntile + 1) >> 1;
  const int pair = g >> 1, rank = cta & 1;
  const int nt = pair % kNTiles, m0 = (2 * (pair / kNTiles) + rank) * 128;

  PROF_BEGIN();
  PROFG(30);
  XLoader xload;
  uint32_t rowoff, xa[12];
  float w06, bias;
  uint4 t4;
  uint32_t w0raw, braw;
  auto load_cin_consts = [&]() {
    rowoff = ld_early32(&tab->rowoff[(tid & 127) >> 3]);
    t4 = ld_early128(tab->ldsm[lane]);
    w0raw = ld_early16(wout + 24 + ((lane & 3) >> 1));
    braw = ld_early16(bout);
  };
  auto expand_cin_consts = [&]() {
#pragma unroll
    for (int i = 0; i < 12; i++) xa[i] = (((i < 4 ? t4.x : i < 8 ? t4.y : t4.z) >> (8 * (i & 3))) & 255) * 16 + (tid & 96);
    w06 = (lane & 1) ? 0.f : __uint_as_float(w0raw << 16);
    bias = __uint_as_float(braw << 16);
    xload.init(table, rowoff);
  };

  auto init_barriers = [&]() {
#pragma unroll
    for (int i = 0; i < kNumBars; i++) mbar_init(bars + 8 * i, i < kBarEmpty ? 129 : i < kBarImg ? 4 : i < kBarX ? 1 : 128);
    asm volatile("fence.mbarrier_init.release.cluster;" ::: "memory");
  };

  uint2 cur[8];
  const int* ip = idx + (m0 + ((tid & 127) >> 3)) * kF;
#pragma unroll
  for (int i = 0; i < 8; i++)
    asm volatile("{.reg .pred p; setp.ne.u32 p, %3, 0; mov.b32 %0, 0; mov.b32 %1, 0; @p ld.global.nc.v2.u32 {%0,%1}, [%2];}"
                 : "=r"(cur[i].x), "=r"(cur[i].y) : "l"(ip + 16 * i * kF), "r"((uint32_t)(gemm && tid < 128)));
  PROF(1);

  if (gemm) {
    if (tid == 128) init_barriers();
    if (tid == 96) asm volatile("prefetch.tensormap [%0];" ::"l"(&tmW) : "memory");
    __syncwarp();
    asm volatile("barrier.cluster.arrive.relaxed.aligned;\nbarrier.cluster.wait.aligned;" ::: "memory");
    PROF(23 + wg);
    if (wg == 0) {
      const uint32_t dst0 = sbase + (tid >> 3) * 128 + (((tid & 7) ^ ((tid >> 3) & 7)) << 4);
      const uint8_t* src0 = table + (tid & 7) * 16;
      uint32_t si[3] = {0, 0, 0};
      auto load_w = [&](int kb) {
        if (tid == 96) {
          const uint32_t full = bars + 8 * (kBarFull + (kb & 3));
          const uint32_t bd = sbase + (kb & 3) * kStageBytes + kABytes + rank * 16384;
          mbar_expect_tx(full, 32768);
          tma_load_mc(bd, &tmW, nt * 256 + rank * 128, kb * 64, full);
          tma_load_mc(bd + 8192, &tmW, nt * 256 + rank * 128 + 64, kb * 64, full);
        }
      };
#pragma unroll 1
      for (int f2 = 0; f2 < kF / 2; f2++) {
        const uint8_t* rp[8];
        uint32_t odd[8];
#pragma unroll
        for (int s = 0; s < kStages; s++) {
          const int kb = 4 * f2 + s;
          const uint32_t full = bars + 8 * (kBarFull + s);
          mbar_wait(bars + 8 * (kBarEmpty + s), (f2 & 1) ^ 1);
          if (kb == 2) mbar_wait(bars + 8 * kBarFull, 0);
          if (kb != 1) load_w(kb);
          if (s == 0) {
#pragma unroll
            for (int i = 0; i < 8; i++) {
              rp[i] = row_ptr(src0, cur[i].x);
              odd[i] = cur[i].y;
            }
            if (kb == 0) PROF(29);
          } else if (s == 2) {
#pragma unroll
            for (int i = 0; i < 8; i++) rp[i] = row_ptr(src0, odd[i]);
          }
#pragma unroll
          for (int i = 0; i < 8; i++) cp_async16(dst0 + s * kStageBytes + i * 2048, rp[i] + (s & 1) * 128);
          cp_async_arrive(full);
          if (s == 1) {
            const int fn = 2 * min(f2 + 1, kF / 2 - 1);
#pragma unroll
            for (int i = 0; i < 8; i++) cur[i] = ld_early64(ip + 16 * i * kF + fn);
          }
          if (kb == 0) PROF(26);
          if (kb == 1) load_w(1);
        }
        if (f2 == 0) PROF(27);
        if (f2 == 1) {
          load_cin_consts();
          load_half_rows<128>(si, idx, tile0, ntile, tid);
        } else if (f2 == 2) {
          static_assert(kGemmTiles * 32 <= 3 * 128 && (kPrepBase + 1) * 32 <= 3 * kThreads, "three table words per thread");
          store_half_rows<128>(s_idx, si, tile0, ntile, tid);
          ones_rows(smem, tid);
          bar_sync<1, 128>();
          bar_arrive<2, 256>();
          bar_arrive<4, 256>();
          expand_cin_consts();
#pragma unroll
          for (int w = 0; w < 3; w++) xload(sbase, w, w, 0);
        } else if (f2 == 8 && tid == 0) {
          await_image(scr);
          ack_image(scr);
        }
      }
      PROF(3);
#pragma unroll 1
      for (int p = 0; p < 4; p++) {
        mbar_wait(bars + 8 * (kBarEmpty + p), 0);
        if (tid == 0) load_image_part(sbase, scr, p);
      }
      PROF(4);
    } else {
      float acc[128];
      {
        const uint32_t* bp = reinterpret_cast<const uint32_t*>(b1 + nt * 256) + (lane & 3);
#pragma unroll
        for (int nb = 0; nb < 32; nb++) {
          const uint32_t b2 = ld_early32(bp + 4 * nb);
          acc[4 * nb] = acc[4 * nb + 2] = __uint_as_float(b2 << 16);
          acc[4 * nb + 1] = acc[4 * nb + 3] = __uint_as_float(b2 & 0xffff0000u);
        }
        if (wg == 1) {
          const uint32_t ww = ld_early32(reinterpret_cast<const uint32_t*>(w2 + nt * 256) + tid - 128);
          *reinterpret_cast<float2*>(smem + kOffEpi + (tid - 128) * 8) =
              make_float2(0.5f * __uint_as_float(ww << 16), 0.5f * __uint_as_float(ww & 0xffff0000u));
        }
        bar_sync<5, 256>();
        pin(acc);
      }
      const uint64_t dA = make_desc(sbase + (wg - 1) * 8192, 16, 1024, 1);
      const uint64_t dB = make_desc(sbase + kABytes, 8192, 1024, 1);
#pragma unroll 1
      for (int kb = 0; kb < kKBlocks; kb++) {
        const int s = kb & 3;
        mbar_wait(bars + 8 * (kBarFull + s), (kb >> 2) & 1);
        if (kb == 0) PROF(4 + wg);
        const bool held = kb == kKBlocks - kStages && wg == 2;
        if (held) {
          wg_wait<0>();
          if ((tid & 95) == 0) mbar_arrive_cluster(bars + 8 * (kBarEmpty + 3), (tid >> 5) & 1);
          bar_sync<3, 256>();
        }
        fence_async_smem();
        wg_fence();
        const uint64_t so = (uint64_t)(s * (kStageBytes >> 4));
#pragma unroll
        for (int k = 0; k < 4; k++) wgmma_ss256(acc, dA + so + k * 2, dB + so + k * 128);
        wg_commit();
        if (kb == kKBlocks - 1 && wg == 1) bar_arrive<3, 256>();
        wg_wait<1>();
        if (kb > 0 && !held && (tid & 95) == 0) mbar_arrive_cluster(bars + 8 * (kBarEmpty + ((kb - 1) & 3)), (tid >> 5) & 1);
      }
      wg_wait<0>();
      pin(acc);
      if ((tid & 95) == 0) mbar_arrive_cluster(bars + 8 * (kBarEmpty + 3), (tid >> 5) & 1);
      PROF(6 + wg);
      if (wg == 1) bar_sync<2, 256>(); else bar_sync<4, 256>();
      load_cin_consts();
      float r0 = 0.f, r1 = 0.f, r2 = 0.f, r3 = 0.f;
      const float2* epi = reinterpret_cast<const float2*>(smem + kOffEpi) + (lane & 3);
#pragma unroll
      for (int nb = 0; nb < 32; nb++) {
        const float2 e = epi[nb * 4];
        float gl[4];
#pragma unroll
        for (int j = 0; j < 4; j++) {
          const float v = acc[4 * nb + j];
          const float arg = v * fmaf(v * v, 0.0356774081f, 0.7978845608f);
          float t;
          asm("tanh.approx.f32 %0, %1;" : "=f"(t) : "f"(arg));
          gl[j] = fmaf(v, t, v);
        }
        r0 = fmaf(gl[0], e.x, r0);
        r2 = fmaf(gl[1], e.y, r2);
        r1 = fmaf(gl[2], e.x, r1);
        r3 = fmaf(gl[3], e.y, r3);
      }
      r0 += r2;
      r1 += r3;
      r0 += __shfl_xor_sync(0xffffffffu, r0, 1);
      r1 += __shfl_xor_sync(0xffffffffu, r1, 1);
      r0 += __shfl_xor_sync(0xffffffffu, r0, 2);
      r1 += __shfl_xor_sync(0xffffffffu, r1, 2);
      if ((lane & 3) < 2) {
        const int row = m0 + (wg - 1) * 64 + warp * 16 + (lane >> 2) + 8 * (lane & 1);
        publish(scr->dnn + row * kSlots + nt, (lane & 1) ? r1 : r0);
      }
      expand_cin_consts();
      PROF(8 + wg);
    }
    __syncwarp();
    asm volatile("barrier.cluster.arrive.relaxed.aligned;" ::: "memory");
  } else {
    if (tid == 352) {
      mbar_init(bars + 8 * kBarPrep, 1);
      fence_async_smem();
      mbar_expect_tx(bars + 8 * kBarPrep, kLayer * 2);
      bulk_load(sbase + kPrepW5, wcin + 5 * kLayer, kLayer * 2, bars + 8 * kBarPrep);
      init_barriers();
    }
    __syncwarp();
    stage_weights(cta, sbase, wcin, wout);
    PROF(2);
    const uint32_t ab = ld_early16(&tab->sent[tid]);
    const uint2 jr = item_rows(tab, tid < 320 ? tid : min((tid & 31) >> 1, 12));
    load_cin_consts();
    uint32_t si[3];
    load_half_rows<kThreads>(si, idx, tile0, ntile, tid);
    PROF(34 + wg);
    cp_async_wait_all();
    __syncthreads();
    PROF(37 + wg);
    build_full_stages(cta, smem, scr->img, jr);
    store_half_rows<kThreads>(s_idx, si, tile0, ntile, tid);
    ones_rows(smem, tid);
    expand_cin_consts();
    PROF(26 + wg);
    mbar_wait(bars + 8 * kBarPrep, 0);
    PROF(40 + wg);
    build_image(cta, smem, scr->img, ab);
    __syncthreads();
    PROF(3 + wg);
    if (tid == 352) {
      red_release(&scr->cnt[0]);
      await_image(scr);
      PROFU(6);
      fence_async_smem();
      for (int p = 0; p < 4; p++) load_image_part(sbase, scr, p);
      PROFU(7);
    }
    __syncwarp();
    xload(sbase, wg, wg, 0);
    if (tid == 352) ack_image(scr);
  }
  __syncwarp();

  {
    float* s_red = reinterpret_cast<float*>(smem + kOffRed) + (tid & 127);

    int wgu;
    asm volatile("shfl.sync.idx.b32 %0, %1, 0, 31, 0xffffffff;" : "=r"(wgu) : "r"(tid >> 7));
    PROF(11 + wg);
    cin_loop((ntile - wgu + 2) / 3, xa, sbase + kOffX + 2 * wgu * kXBufBytes, w06, sbase, bars + 8 * kBarImg,
             [&](int it) { mbar_wait(bars + 8 * (kBarX + wgu), it & 1); },
             [&](int it) { xload(sbase, min(wgu + 3 * it + 3, ntile - 1), wgu, (it + 1) & 1); },
             [&] { cp_async16_if(tid < 5 * nsamp, sbase + kOffDnn + tid * 16, scr->dnn + samp0 * kSlots + tid * 4); },
             [&](int it, float v) {
               const int tile = wgu + 3 * it;
               s_red[(toff + tile) * 128] = v;
               if (tile < toff) {
#pragma unroll
                 for (int o = 16; o > 0; o >>= 1) v += __shfl_xor_sync(0xffffffffu, v, o);
                 if (lane == 0) publish(scr->dnn + samp0 * kSlots + kNTiles + warp, v);
               }
               PROFU(90 + tile);
             });
  }
  PROF(17 + wg);
  cp_async_wait_all();
  __syncthreads();
  {
    static_assert(kMaxSamples <= kThreads / 16, "one pass");
    const int sl = toff + (tid >> 4), l = tid & 15;
    const bool live = sl < nsamp, whole = 2 * sl + 1 < toff + ntile;
    float c = 0.f;
    if (live) {
      const float4* rp = reinterpret_cast<const float4*>(smem + kOffRed + sl * 1024) + l;
      const float4 p0 = rp[0], p1 = rp[16];
      c = ((p0.x + p0.y) + (p0.z + p0.w)) + ((p1.x + p1.y) + (p1.z + p1.w));
      if (whole) {
        const float4 p2 = rp[32], p3 = rp[48];
        c += ((p2.x + p2.y) + (p2.z + p2.w)) + ((p3.x + p3.y) + (p3.z + p3.w));
      }
#pragma unroll 1
      for (int k = l; k < (whole ? kNTiles : kNTiles + 4); k += 16) {
        float* gp = scr->dnn + (samp0 + sl) * kSlots + k;
        uint32_t bits = *reinterpret_cast<const uint32_t*>(smem + kOffDnn + (sl * kSlots + k) * 4);
        for (uint32_t n = 0; bits == 0; n++) {
          asm volatile("ld.relaxed.gpu.global.u32 %0, [%1];" : "=r"(bits) : "l"(gp) : "memory");
          if (n > (1u << 22)) __trap();
        }
        c += __uint_as_float(bits);
        *gp = 0.f;
      }
    }
    __syncwarp();
#pragma unroll
    for (int o = 8; o > 0; o >>= 1) c += __shfl_xor_sync(0xffffffffu, c, o);
    if (live && l == 0) out[samp0 + sl] = f2bf(c + bias);
  }
  PROF(20 + wg);
  PROFG(31);
  PROF_END();
  __syncwarp();
  if (gemm) asm volatile("barrier.cluster.wait.aligned;" ::: "memory");
}

typedef CUresult (*EncodeFn)(CUtensorMap*, CUtensorMapDataType, cuuint32_t, void*, const cuuint64_t*, const cuuint64_t*,
                             const cuuint32_t*, const cuuint32_t*, CUtensorMapInterleave, CUtensorMapSwizzle,
                             CUtensorMapL2promotion, CUtensorMapFloatOOBfill);

}

extern "C" void kernel_launch(void* const* d_in, const int* in_sizes, int n_in, void* d_out, int out_size) {
  (void)in_sizes; (void)n_in; (void)out_size;
  static EncodeFn encode = nullptr;
  static void* scr = nullptr;
  static void* tab = nullptr;
  if (!encode) {
    cudaGetSymbolAddress(&scr, g_scratch);
    cudaGetSymbolAddress(&tab, g_tab);
    void* fn = nullptr;
    cudaDriverEntryPointQueryResult st;
    cudaGetDriverEntryPoint("cuTensorMapEncodeTiled", &fn, cudaEnableDefault, &st);
    encode = reinterpret_cast<EncodeFn>(fn);
    cudaFuncSetAttribute(xdeepfm_kernel, cudaFuncAttributeMaxDynamicSharedMemorySize, kSmemBytes);
  }
  CUtensorMap tm;
  const cuuint64_t dims[2] = {(cuuint64_t)kDin, (cuuint64_t)kDin};
  const cuuint64_t strides[1] = {(cuuint64_t)kDin * 2};
  const cuuint32_t box[2] = {64, 64};
  const cuuint32_t estr[2] = {1, 1};
  encode(&tm, CU_TENSOR_MAP_DATA_TYPE_BFLOAT16, 2, d_in[4], dims, strides, box, estr, CU_TENSOR_MAP_INTERLEAVE_NONE,
         CU_TENSOR_MAP_SWIZZLE_128B, CU_TENSOR_MAP_L2_PROMOTION_L2_256B, CU_TENSOR_MAP_FLOAT_OOB_FILL_NONE);
  xdeepfm_kernel<<<kCtas, kThreads, kSmemBytes>>>(
      tm, (const int*)d_in[0], (const uint8_t*)d_in[1], (const uint16_t*)d_in[2], (const uint16_t*)d_in[3],
      (const uint16_t*)d_in[5], (const uint16_t*)d_in[6], (const uint16_t*)d_in[7], (uint16_t*)d_out,
      (Scratch*)scr, (const Tables*)tab);
}
```
